```python
import torch

def _softmax(x, axis=-1):
    return torch.softmax(x, dim=axis)
def _gelu(x):
    return torch.nn.functional.gelu(x, approximate="tanh")
def _silu(x):
    return torch.nn.functional.silu(x)
def _sigmoid(x):
    return torch.sigmoid(x)
def _layernorm(x, axis=-1, eps=1e-5):
    m = x.mean(dim=axis, keepdim=True)
    v = x.var(dim=axis, keepdim=True, unbiased=False)
    return (x - m) / torch.sqrt(v + eps)
def _scatter_add(tgt, idx, src, axis=0):
    return tgt.clone().index_add_(axis, idx, src)
def _segment_sum(src, seg, n):
    out = torch.zeros((n,) + src.shape[1:], dtype=src.dtype)
    return out.index_add_(0, seg, src)
def _pad(x, pw):
    flat = tuple(v for pair in reversed(pw) for v in pair)
    return torch.nn.functional.pad(x, flat)

kernel_name = 'sequential_preLN__spectral_gfnet__mixer_token_mlp__prompt'

def setup_inputs():

    _w = (lambda a: (lambda t: t.to(torch.bfloat16) if t.is_floating_point() else t)(torch.as_tensor(a)))
    def _A_setup():
        B, S, D = 1, 2048, 448
        Df = D // 2 + 1
        return {
            "x": _w((lambda *s: torch.randn(*s, dtype=torch.bfloat16) * 0.05)(B, S, D)),
            "w_r": _w((lambda *s: torch.randn(*s, dtype=torch.bfloat16) * 0.4)(S, Df) * 0.02),
            "w_i": _w((lambda *s: torch.randn(*s, dtype=torch.bfloat16) * 0.4)(S, Df) * 0.02),
        }
    _A_in = _A_setup()

    def _B_setup():
        B, S, D, F = 1, 2048, 448, 1792
        return {
            "x": _w((lambda *s: torch.randn(*s, dtype=torch.bfloat16) * 0.05)(B, S, D)),
            "w1": _w((lambda *s: torch.randn(*s, dtype=torch.bfloat16) * 0.4)(S, F) * (S ** -0.5)),
            "b1": _w((lambda *s: torch.randn(*s, dtype=torch.bfloat16) * 3.2)(F) * 0.02),
            "w2": _w((lambda *s: torch.randn(*s, dtype=torch.bfloat16) * 0.2)(F, S) * (F ** -0.5)),
            "b2": _w((lambda *s: torch.randn(*s, dtype=torch.bfloat16) * 0.4)(S) * 0.02),
        }
    _B_in = _B_setup()

    return {
        "A_x": _A_in["x"],
        "A_w_r": _A_in["w_r"],
        "A_w_i": _A_in["w_i"],
        "B_x": _B_in["x"],
        "B_w1": _B_in["w1"],
        "B_b1": _B_in["b1"],
        "B_w2": _B_in["w2"],
        "B_b2": _B_in["b2"],
    }

def reference(A_x, A_w_r, A_w_i, B_x, B_w1, B_b1, B_w2, B_b2):
    def _A_ref(x, w_r, w_i):
        B, S, D = x.shape
        X = (lambda x, axes=(-2,-1): torch.fft.rfft2(x.float(), dim=axes))(x, axes=(-2, -1))
        W = w_r + 1j * w_i
        X = X * W
        y = (lambda x, s, axes=(-2,-1): torch.fft.irfft2(x, s=s, dim=axes).to(torch.bfloat16))(X, (S, D), axes=(-2, -1))
        return y

    def _B_ref(x, w1, b1, w2, b2):
        B, S, D = x.shape
        h = _layernorm(x, axis=-1)
        u = torch.einsum("bsd,sf->bdf", h, w1) + b1
        u = _gelu(u)
        y = torch.einsum("bdf,fs->bds", u, w2) + b2
        return (lambda x, *d: x.permute(*d))(y, 0, 2, 1)

    x = A_x
    h = x + _A_ref(_layernorm(x, axis=-1), A_w_r, A_w_i)
    h2 = h + _B_ref(_layernorm(h, axis=-1), B_w1, B_b1, B_w2, B_b2)
    return h2
```

```cpp
#include <cuda_runtime.h>
#include <cuda_bf16.h>
#include <cuda.h>
#include <stdint.h>

namespace {

constexpr int NCTA = 128;
constexpr int NTHR = 384;
constexpr int NW = 12;
constexpr int NA = 9;
constexpr int WST = 8192, AST = 14336;
constexpr int OFF_A = NW * WST;
constexpr int OFF_T = OFF_A;
constexpr int OFF_XS = OFF_A + 15872;
constexpr int OFF_WR = OFF_XS + 17920;
constexpr int OFF_WI = OFF_WR + 10240;
constexpr int OFF_BT = OFF_WI + 10240;
constexpr int OFF_TAB = OFF_BT + 16384;
constexpr int OFF_BAR = OFF_A + NA * AST;
constexpr int OFF_MISC = OFF_BAR + 1280;
constexpr int OFF_CS = OFF_TAB + 12800;
constexpr int SMEM_BYTES = OFF_MISC + 64;
constexpr int TPA = 452, TPC = 228;
constexpr int OFF_HS = OFF_A + (NA - 1) * AST;
static_assert(OFF_CS + 2048 <= OFF_HS, "fft scratch");
static_assert(SMEM_BYTES <= 232448, "smem");
constexpr int SPIN_LIMIT = 20000;

__device__ const uint4 g_tab[25*32] = {
{0x3f80,0x3f80,0x3f80,0x3f80}, {0x3f80,0xbf80,0x3f80,0xbf80},
{0x3f80,0x3f80,0x3f80,0x3f80}, {0x3f80,0xbf80,0x3f80,0xbf80},
{0x3f80,0x3f80,0x3f800000,0x3f800000}, {0x3ec43f6d,0xbec4bf6d,0x3f6dbec4,0xbf6d3ec4},
{0x3f353f35,0x3f353f35,0x3f35bf35,0x3f35bf35}, {0x3f6d3ec4,0xbf6dbec4,0x3ec4bf6d,0xbec43f6d},
{0x3f80,0x3f80,0xbf80,0xbf80}, {0x3f353f35,0xbf35bf35,0xbf35bf35,0x3f353f35},
{0x3f800000,0x3f800000,0xbf800000,0xbf800000}, {0x3f35bf35,0xbf353f35,0xbf353f35,0x3f35bf35},
{0x3f80,0x3f80,0xbf800000,0xbf800000}, {0x3f6d3ec4,0xbf6dbec4,0xbec43f6d,0x3ec4bf6d},
{0x3f35bf35,0x3f35bf35,0x3f353f35,0x3f353f35}, {0xbec4bf6d,0x3ec43f6d,0x3f6dbec4,0xbf6d3ec4},
{0x3f80,0x3f80,0x3f80,0x3f80}, {0x3f800000,0xbf800000,0x3f800000,0xbf800000},
{0xbf80,0xbf80,0xbf80,0xbf80}, {0xbf800000,0x3f800000,0xbf800000,0x3f800000},
{0x3f80,0x3f80,0x3f800000,0x3f800000}, {0x3f6dbec4,0xbf6d3ec4,0xbec4bf6d,0x3ec43f6d},
{0xbf35bf35,0xbf35bf35,0xbf353f35,0xbf353f35}, {0xbec43f6d,0x3ec4bf6d,0x3f6d3ec4,0xbf6dbec4},
{0x3f80,0x3f80,0xbf80,0xbf80}, {0x3f35bf35,0xbf353f35,0xbf353f35,0x3f35bf35},
{0xbf800000,0xbf800000,0x3f800000,0x3f800000}, {0x3f353f35,0xbf35bf35,0xbf35bf35,0x3f353f35},
{0x3f80,0x3f80,0xbf800000,0xbf800000}, {0x3ec4bf6d,0xbec43f6d,0x3f6d3ec4,0xbf6dbec4},
{0xbf353f35,0xbf353f35,0xbf35bf35,0xbf35bf35}, {0x3f6dbec4,0xbf6d3ec4,0x3ec43f6d,0xbec4bf6d},
{0x3f80,0x3f80,0x3f80,0x3f80}, {0x3f80,0xbf80,0x3f80,0xbf80},
{0x3f80,0x3f80,0x3f80,0x3f80}, {0x3f80,0xbf80,0x3f80,0xbf80},
{0xbf80,0xbf80,0xbf800000,0xbf800000}, {0xbec4bf6d,0x3ec43f6d,0xbf6d3ec4,0x3f6dbec4},
{0xbf35bf35,0xbf35bf35,0xbf353f35,0xbf353f35}, {0xbf6dbec4,0x3f6d3ec4,0xbec43f6d,0x3ec4bf6d},
{0x3f80,0x3f80,0xbf80,0xbf80}, {0x3f353f35,0xbf35bf35,0xbf35bf35,0x3f353f35},
{0x3f800000,0x3f800000,0xbf800000,0xbf800000}, {0x3f35bf35,0xbf353f35,0xbf353f35,0x3f35bf35},
{0xbf80,0xbf80,0x3f800000,0x3f800000}, {0xbf6dbec4,0x3f6d3ec4,0x3ec4bf6d,0xbec43f6d},
{0xbf353f35,0xbf353f35,0xbf35bf35,0xbf35bf35}, {0x3ec43f6d,0xbec4bf6d,0xbf6d3ec4,0x3f6dbec4},
{0x3f80,0x3f80,0x3f80,0x3f80}, {0x3f800000,0xbf800000,0x3f800000,0xbf800000},
{0xbf80,0xbf80,0xbf80,0xbf80}, {0xbf800000,0x3f800000,0xbf800000,0x3f800000},
{0xbf80,0xbf80,0xbf800000,0xbf800000}, {0xbf6d3ec4,0x3f6dbec4,0x3ec43f6d,0xbec4bf6d},
{0x3f353f35,0x3f353f35,0x3f35bf35,0x3f35bf35}, {0x3ec4bf6d,0xbec43f6d,0xbf6dbec4,0x3f6d3ec4},
{0x3f80,0x3f80,0xbf80,0xbf80}, {0x3f35bf35,0xbf353f35,0xbf353f35,0x3f35bf35},
{0xbf800000,0xbf800000,0x3f800000,0x3f800000}, {0x3f353f35,0xbf35bf35,0xbf35bf35,0x3f353f35},
{0xbf80,0xbf80,0x3f800000,0x3f800000}, {0xbec43f6d,0x3ec4bf6d,0xbf6dbec4,0x3f6d3ec4},
{0x3f35bf35,0x3f35bf35,0x3f353f35,0x3f353f35}, {0xbf6d3ec4,0x3f6dbec4,0xbec4bf6d,0x3ec43f6d},
{0x3f800000,0x3f800000,0x3f800000,0x3f800000}, {0x3f800000,0xbf800000,0x3f800000,0xbf800000},
{0x3f800000,0x3f800000,0x3f800000,0x3f800000}, {0x3f800000,0xbf800000,0x3f800000,0xbf800000},
{0x3f800000,0x3f800000,0xbf80,0xbf80}, {0x3f6dbec4,0xbf6d3ec4,0xbec4bf6d,0x3ec43f6d},
{0x3f35bf35,0x3f35bf35,0xbf35bf35,0xbf35bf35}, {0x3ec4bf6d,0xbec43f6d,0xbf6dbec4,0x3f6d3ec4},
{0x3f800000,0x3f800000,0xbf800000,0xbf800000}, {0x3f35bf35,0xbf353f35,0xbf353f35,0x3f35bf35},
{0xbf80,0xbf80,0x3f80,0x3f80}, {0xbf35bf35,0x3f353f35,0x3f353f35,0xbf35bf35},
{0x3f800000,0x3f800000,0x3f80,0x3f80}, {0x3ec4bf6d,0xbec43f6d,0x3f6d3ec4,0xbf6dbec4},
{0xbf35bf35,0xbf35bf35,0x3f35bf35,0x3f35bf35}, {0xbf6d3ec4,0x3f6dbec4,0xbec4bf6d,0x3ec43f6d},
{0x3f800000,0x3f800000,0x3f800000,0x3f800000}, {0xbf80,0x3f80,0xbf80,0x3f80},
{0xbf800000,0xbf800000,0xbf800000,0xbf800000}, {0x3f80,0xbf80,0x3f80,0xbf80},
{0x3f800000,0x3f800000,0xbf80,0xbf80}, {0xbec4bf6d,0x3ec43f6d,0xbf6d3ec4,0x3f6dbec4},
{0xbf353f35,0xbf353f35,0x3f353f35,0x3f353f35}, {0x3f6d3ec4,0xbf6dbec4,0x3ec4bf6d,0xbec43f6d},
{0x3f800000,0x3f800000,0xbf800000,0xbf800000}, {0xbf35bf35,0x3f353f35,0x3f353f35,0xbf35bf35},
{0x3f80,0x3f80,0xbf80,0xbf80}, {0x3f35bf35,0xbf353f35,0xbf353f35,0x3f35bf35},
{0x3f800000,0x3f800000,0x3f80,0x3f80}, {0xbf6dbec4,0x3f6d3ec4,0x3ec4bf6d,0xbec43f6d},
{0x3f353f35,0x3f353f35,0xbf353f35,0xbf353f35}, {0xbec4bf6d,0x3ec43f6d,0x3f6dbec4,0xbf6d3ec4},
{0x3f800000,0x3f800000,0x3f800000,0x3f800000}, {0x3f800000,0xbf800000,0x3f800000,0xbf800000},
{0x3f800000,0x3f800000,0x3f800000,0x3f800000}, {0x3f800000,0xbf800000,0x3f800000,0xbf800000},
{0xbf800000,0xbf800000,0x3f80,0x3f80}, {0xbf6d3ec4,0x3f6dbec4,0x3ec43f6d,0xbec4bf6d},
{0xbf353f35,0xbf353f35,0x3f353f35,0x3f353f35}, {0xbec43f6d,0x3ec4bf6d,0x3f6d3ec4,0xbf6dbec4},
{0x3f800000,0x3f800000,0xbf800000,0xbf800000}, {0x3f35bf35,0xbf353f35,0xbf353f35,0x3f35bf35},
{0xbf80,0xbf80,0x3f80,0x3f80}, {0xbf35bf35,0x3f353f35,0x3f353f35,0xbf35bf35},
{0xbf800000,0xbf800000,0xbf80,0xbf80}, {0xbec43f6d,0x3ec4bf6d,0xbf6dbec4,0x3f6d3ec4},
{0x3f353f35,0x3f353f35,0xbf353f35,0xbf353f35}, {0x3f6dbec4,0xbf6d3ec4,0x3ec43f6d,0xbec4bf6d},
{0x3f800000,0x3f800000,0x3f800000,0x3f800000}, {0xbf80,0x3f80,0xbf80,0x3f80},
{0xbf800000,0xbf800000,0xbf800000,0xbf800000}, {0x3f80,0xbf80,0x3f80,0xbf80},
{0xbf800000,0xbf800000,0x3f80,0x3f80}, {0x3ec43f6d,0xbec4bf6d,0x3f6dbec4,0xbf6d3ec4},
{0x3f35bf35,0x3f35bf35,0xbf35bf35,0xbf35bf35}, {0xbf6dbec4,0x3f6d3ec4,0xbec43f6d,0x3ec4bf6d},
{0x3f800000,0x3f800000,0xbf800000,0xbf800000}, {0xbf35bf35,0x3f353f35,0x3f353f35,0xbf35bf35},
{0x3f80,0x3f80,0xbf80,0xbf80}, {0x3f35bf35,0xbf353f35,0xbf353f35,0x3f35bf35},
{0xbf800000,0xbf800000,0xbf80,0xbf80}, {0x3f6d3ec4,0xbf6dbec4,0xbec43f6d,0x3ec4bf6d},
{0xbf35bf35,0xbf35bf35,0x3f35bf35,0x3f35bf35}, {0x3ec43f6d,0xbec4bf6d,0xbf6d3ec4,0x3f6dbec4},
{0x3f800000,0x0,0x3f800000,0x0}, {0x3f800000,0x0,0x3f800000,0x0},
{0x3f800000,0x0,0x3f800000,0x0}, {0x3f800000,0x0,0x3f800000,0x0},
{0x3f800000,0x0,0x3f7fb10f,0xbd48fb30}, {0x3f7ec46d,0xbdc8bd36,0x3f7d3aac,0xbe164083},
{0x3f7b14be,0xbe47c5c2,0x3f7853f8,0xbe78cfcc}, {0x3f74fa0b,0xbe94a031,0x3f710908,0xbeac7cd4},
{0x3f800000,0x0,0x3f7ec46d,0xbdc8bd36}, {0x3f7b14be,0xbe47c5c2,0x3f74fa0b,0xbe94a031},
{0x3f6c835e,0xbec3ef15,0x3f61c598,0xbef15aea}, {0x3f54db31,0xbf0e39da,0x3f45e403,0xbf226799},
{0x3f800000,0x0,0x3f7d3aac,0xbe164083}, {0x3f74fa0b,0xbe94a031,0x3f676bd8,0xbedae880},
{0x3f54db31,0xbf0e39da,0x3f3daef9,0xbf2beb4a}, {0x3f226799,0xbf45e403,0x3f039c3d,0xbf5b941a},
{0x3f800000,0x0,0x3f7b14be,0xbe47c5c2}, {0x3f6c835e,0xbec3ef15,0x3f54db31,0xbf0e39da},
{0x3f3504f3,0xbf3504f3,0x3f0e39da,0xbf54db31}, {0x3ec3ef15,0xbf6c835e,0x3e47c5c2,0xbf7b14be},
{0x3f800000,0x0,0x3f7853f8,0xbe78cfcc}, {0x3f61c598,0xbef15aea,0x3f3daef9,0xbf2beb4a},
{0x3f0e39da,0xbf54db31,0x3eac7cd4,0xbf710908}, {0x3dc8bd36,0xbf7ec46d,0xbe164083,0xbf7d3aac},
{0x3f800000,0x0,0x3f74fa0b,0xbe94a031}, {0x3f54db31,0xbf0e39da,0x3f226799,0xbf45e403},
{0x3ec3ef15,0xbf6c835e,0x3dc8bd36,0xbf7ec46d}, {0xbe47c5c2,0xbf7b14be,0xbef15aea,0xbf61c598},
{0x3f800000,0x0,0x3f710908,0xbeac7cd4}, {0x3f45e403,0xbf226799,0x3f039c3d,0xbf5b941a},
{0x3e47c5c2,0xbf7b14be,0xbe164083,0xbf7d3aac}, {0xbef15aea,0xbf61c598,0xbf3daef9,0xbf2beb4a},
{0x3f800000,0x0,0x3f6c835e,0xbec3ef15}, {0x3f3504f3,0xbf3504f3,0x3ec3ef15,0xbf6c835e},
{0x0,0xbf800000,0xbec3ef15,0xbf6c835e}, {0xbf3504f3,0xbf3504f3,0xbf6c835e,0xbec3ef15},
{0x3f800000,0x0,0x3f676bd8,0xbedae880}, {0x3f226799,0xbf45e403,0x3e78cfcc,0xbf7853f8},
{0xbe47c5c2,0xbf7b14be,0xbf187fc0,0xbf4d9f02}, {0xbf61c598,0xbef15aea,0xbf7fb10f,0xbd48fb30},
{0x3f800000,0x0,0x3f61c598,0xbef15aea}, {0x3f0e39da,0xbf54db31,0x3dc8bd36,0xbf7ec46d},
{0xbec3ef15,0xbf6c835e,0xbf45e403,0xbf226799}, {0xbf7b14be,0xbe47c5c2,0xbf74fa0b,0x3e94a031},
{0x3f800000,0x0,0x3f5b941a,0xbf039c3d}, {0x3ef15aea,0xbf61c598,0xbd48fb30,0xbf7fb10f},
{0xbf0e39da,0xbf54db31,0xbf676bd8,0xbedae880}, {0xbf7ec46d,0x3dc8bd36,0xbf4d9f02,0x3f187fc0},
{0x3f800000,0x0,0x3f54db31,0xbf0e39da}, {0x3ec3ef15,0xbf6c835e,0xbe47c5c2,0xbf7b14be},
{0xbf3504f3,0xbf3504f3,0xbf7b14be,0xbe47c5c2}, {0xbf6c835e,0x3ec3ef15,0xbf0e39da,0x3f54db31},
{0x3f800000,0x0,0x3f4d9f02,0xbf187fc0}, {0x3e94a031,0xbf74fa0b,0xbeac7cd4,0xbf710908},
{0xbf54db31,0xbf0e39da,0xbf7fb10f,0x3d48fb30}, {0xbf45e403,0x3f226799,0xbe78cfcc,0x3f7853f8},
{0x3f800000,0x0,0x3f45e403,0xbf226799}, {0x3e47c5c2,0xbf7b14be,0xbef15aea,0xbf61c598},
{0xbf6c835e,0xbec3ef15,0xbf74fa0b,0x3e94a031}, {0xbf0e39da,0x3f54db31,0x3dc8bd36,0x3f7ec46d},
{0x3f800000,0x0,0x3f3daef9,0xbf2beb4a}, {0x3dc8bd36,0xbf7ec46d,0xbf187fc0,0xbf4d9f02},
{0xbf7b14be,0xbe47c5c2,0xbf5b941a,0x3f039c3d}, {0xbe94a031,0x3f74fa0b,0x3edae880,0x3f676bd8},
{0x3f800000,0x0,0x3f800000,0x0}, {0x3f800000,0x0,0x3f800000,0x0},
{0x3f800000,0x0,0x3f800000,0x0}, {0x3f800000,0x0,0x3f800000,0x0},
{0x3f800000,0x0,0x3f7fb10f,0x3d48fb30}, {0x3f7ec46d,0x3dc8bd36,0x3f7d3aac,0x3e164083},
{0x3f7b14be,0x3e47c5c2,0x3f7853f8,0x3e78cfcc}, {0x3f74fa0b,0x3e94a031,0x3f710908,0x3eac7cd4},
{0x3f800000,0x0,0x3f7ec46d,0x3dc8bd36}, {0x3f7b14be,0x3e47c5c2,0x3f74fa0b,0x3e94a031},
{0x3f6c835e,0x3ec3ef15,0x3f61c598,0x3ef15aea}, {0x3f54db31,0x3f0e39da,0x3f45e403,0x3f226799},
{0x3f800000,0x0,0x3f7d3aac,0x3e164083}, {0x3f74fa0b,0x3e94a031,0x3f676bd8,0x3edae880},
{0x3f54db31,0x3f0e39da,0x3f3daef9,0x3f2beb4a}, {0x3f226799,0x3f45e403,0x3f039c3d,0x3f5b941a},
{0x3f800000,0x0,0x3f7b14be,0x3e47c5c2}, {0x3f6c835e,0x3ec3ef15,0x3f54db31,0x3f0e39da},
{0x3f3504f3,0x3f3504f3,0x3f0e39da,0x3f54db31}, {0x3ec3ef15,0x3f6c835e,0x3e47c5c2,0x3f7b14be},
{0x3f800000,0x0,0x3f7853f8,0x3e78cfcc}, {0x3f61c598,0x3ef15aea,0x3f3daef9,0x3f2beb4a},
{0x3f0e39da,0x3f54db31,0x3eac7cd4,0x3f710908}, {0x3dc8bd36,0x3f7ec46d,0xbe164083,0x3f7d3aac},
{0x3f800000,0x0,0x3f74fa0b,0x3e94a031}, {0x3f54db31,0x3f0e39da,0x3f226799,0x3f45e403},
{0x3ec3ef15,0x3f6c835e,0x3dc8bd36,0x3f7ec46d}, {0xbe47c5c2,0x3f7b14be,0xbef15aea,0x3f61c598},
{0x3f800000,0x0,0x3f710908,0x3eac7cd4}, {0x3f45e403,0x3f226799,0x3f039c3d,0x3f5b941a},
{0x3e47c5c2,0x3f7b14be,0xbe164083,0x3f7d3aac}, {0xbef15aea,0x3f61c598,0xbf3daef9,0x3f2beb4a},
{0x3f800000,0x0,0x3f800000,0x0}, {0x3f800000,0x0,0x3f800000,0x0},
{0x3f800000,0x0,0x3f800000,0x0}, {0x3f800000,0x0,0x3f800000,0x0},
{0x3f6c835e,0x3ec3ef15,0x3f676bd8,0x3edae880}, {0x3f61c598,0x3ef15aea,0x3f5b941a,0x3f039c3d},
{0x3f54db31,0x3f0e39da,0x3f4d9f02,0x3f187fc0}, {0x3f45e403,0x3f226799,0x3f3daef9,0x3f2beb4a},
{0x3f3504f3,0x3f3504f3,0x3f226799,0x3f45e403}, {0x3f0e39da,0x3f54db31,0x3ef15aea,0x3f61c598},
{0x3ec3ef15,0x3f6c835e,0x3e94a031,0x3f74fa0b}, {0x3e47c5c2,0x3f7b14be,0x3dc8bd36,0x3f7ec46d},
{0x3ec3ef15,0x3f6c835e,0x3e78cfcc,0x3f7853f8}, {0x3dc8bd36,0x3f7ec46d,0xbd48fb30,0x3f7fb10f},
{0xbe47c5c2,0x3f7b14be,0xbeac7cd4,0x3f710908}, {0xbef15aea,0x3f61c598,0xbf187fc0,0x3f4d9f02},
{0x0,0x3f800000,0xbe47c5c2,0x3f7b14be}, {0xbec3ef15,0x3f6c835e,0xbf0e39da,0x3f54db31},
{0xbf3504f3,0x3f3504f3,0xbf54db31,0x3f0e39da}, {0xbf6c835e,0x3ec3ef15,0xbf7b14be,0x3e47c5c2},
{0xbec3ef15,0x3f6c835e,0xbf187fc0,0x3f4d9f02}, {0xbf45e403,0x3f226799,0xbf676bd8,0x3edae880},
{0xbf7b14be,0x3e47c5c2,0xbf7fb10f,0xbd48fb30}, {0xbf74fa0b,0xbe94a031,0xbf5b941a,0xbf039c3d},
{0xbf3504f3,0x3f3504f3,0xbf61c598,0x3ef15aea}, {0xbf7b14be,0x3e47c5c2,0xbf7ec46d,0xbdc8bd36},
{0xbf6c835e,0xbec3ef15,0xbf45e403,0xbf226799}, {0xbf0e39da,0xbf54db31,0xbe94a031,0xbf74fa0b},
{0xbf6c835e,0x3ec3ef15,0xbf7fb10f,0x3d48fb30}, {0xbf74fa0b,0xbe94a031,0xbf4d9f02,0xbf187fc0},
{0xbf0e39da,0xbf54db31,0xbe78cfcc,0xbf7853f8}, {0x3dc8bd36,0xbf7ec46d,0x3edae880,0xbf676bd8},
{0x3f803f80,0x3f803f80,0x0,0x0}, {0x3f803f80,0x3f803f80,0x0,0x0},
{0x3f803f80,0x3f803f80,0x0,0x0}, {0x3f803f80,0x3f803f80,0x0,0x0},
{0x3f80,0x3f80,0x3f800000,0x3f800000}, {0xbf80,0xbf80,0xbf800000,0xbf800000},
{0x3f80,0x3f80,0x3f800000,0x3f800000}, {0xbf80,0xbf80,0xbf800000,0xbf800000},
{0x3f6d3f80,0xbf6dbf80,0x3ec40000,0xbec40000}, {0x3ec43f35,0xbec4bf35,0x3f6d3f35,0xbf6dbf35},
{0xbec40000,0x3ec40000,0x3f6d3f80,0xbf6dbf80}, {0xbf6dbf35,0x3f6d3f35,0x3ec43f35,0xbec4bf35},
{0xbec43f80,0x3ec4bf80,0x3f6d0000,0xbf6d0000}, {0x3f6dbf35,0xbf6d3f35,0xbec4bf35,0x3ec43f35},
{0xbf6d0000,0x3f6d0000,0xbec43f80,0x3ec4bf80}, {0x3ec43f35,0xbec4bf35,0x3f6dbf35,0xbf6d3f35},
{0x3f353f80,0x3f353f80,0x3f350000,0x3f350000}, {0xbf350000,0xbf350000,0x3f353f80,0x3f353f80},
{0xbf35bf80,0xbf35bf80,0xbf350000,0xbf350000}, {0x3f350000,0x3f350000,0xbf35bf80,0xbf35bf80},
{0xbf353f80,0xbf353f80,0x3f350000,0x3f350000}, {0x3f350000,0x3f350000,0x3f35bf80,0x3f35bf80},
{0x3f35bf80,0x3f35bf80,0xbf350000,0xbf350000}, {0xbf350000,0xbf350000,0xbf353f80,0xbf353f80},
{0x3ec43f80,0xbec4bf80,0x3f6d0000,0xbf6d0000}, {0xbf6dbf35,0x3f6d3f35,0xbec43f35,0x3ec4bf35},
{0x3f6d0000,0xbf6d0000,0xbec4bf80,0x3ec43f80}, {0xbec43f35,0x3ec4bf35,0x3f6d3f35,0xbf6dbf35},
{0xbf6d3f80,0x3f6dbf80,0x3ec40000,0xbec40000}, {0xbec43f35,0x3ec4bf35,0x3f6dbf35,0xbf6d3f35},
{0x3ec40000,0xbec40000,0x3f6dbf80,0xbf6d3f80}, {0x3f6dbf35,0xbf6d3f35,0x3ec4bf35,0xbec43f35},
{0xbf803f80,0xbf803f80,0x0,0x0}, {0xbf803f80,0xbf803f80,0x0,0x0},
{0xbf803f80,0xbf803f80,0x0,0x0}, {0xbf803f80,0xbf803f80,0x0,0x0},
{0x3f80,0x3f80,0xbf800000,0xbf800000}, {0xbf80,0xbf80,0x3f800000,0x3f800000},
{0x3f80,0x3f80,0xbf800000,0xbf800000}, {0xbf80,0xbf80,0x3f800000,0x3f800000},
{0xbf6d3f80,0x3f6dbf80,0xbec40000,0x3ec40000}, {0xbec43f35,0x3ec4bf35,0xbf6d3f35,0x3f6dbf35},
{0x3ec40000,0xbec40000,0xbf6d3f80,0x3f6dbf80}, {0x3f6dbf35,0xbf6d3f35,0xbec43f35,0x3ec4bf35},
{0x3ec43f80,0xbec4bf80,0xbf6d0000,0x3f6d0000}, {0xbf6dbf35,0x3f6d3f35,0x3ec4bf35,0xbec43f35},
{0x3f6d0000,0xbf6d0000,0x3ec43f80,0xbec4bf80}, {0xbec43f35,0x3ec4bf35,0xbf6dbf35,0x3f6d3f35},
{0xbf353f80,0xbf353f80,0xbf350000,0xbf350000}, {0x3f350000,0x3f350000,0xbf353f80,0xbf353f80},
{0x3f35bf80,0x3f35bf80,0x3f350000,0x3f350000}, {0xbf350000,0xbf350000,0x3f35bf80,0x3f35bf80},
{0x3f353f80,0x3f353f80,0xbf350000,0xbf350000}, {0xbf350000,0xbf350000,0xbf35bf80,0xbf35bf80},
{0xbf35bf80,0xbf35bf80,0x3f350000,0x3f350000}, {0x3f350000,0x3f350000,0x3f353f80,0x3f353f80},
{0xbec43f80,0x3ec4bf80,0xbf6d0000,0x3f6d0000}, {0x3f6dbf35,0xbf6d3f35,0x3ec43f35,0xbec4bf35},
{0xbf6d0000,0x3f6d0000,0x3ec4bf80,0xbec43f80}, {0x3ec43f35,0xbec4bf35,0xbf6d3f35,0x3f6dbf35},
{0x3f6d3f80,0xbf6dbf80,0xbec40000,0x3ec40000}, {0x3ec43f35,0xbec4bf35,0xbf6dbf35,0x3f6d3f35},
{0xbec40000,0x3ec40000,0xbf6dbf80,0x3f6d3f80}, {0xbf6dbf35,0x3f6d3f35,0xbec4bf35,0x3ec43f35},
{0x3f803f80,0x0,0x0,0x3f803f80}, {0x3f803f80,0x0,0x0,0x3f803f80},
{0x3f803f80,0x0,0x0,0x3f803f80}, {0x3f803f80,0x0,0x0,0x3f803f80},
{0x3f353f80,0x3f350000,0xbf350000,0x3f353f80}, {0xbf350000,0x3f353f80,0xbf35bf80,0xbf350000},
{0xbf35bf80,0xbf350000,0x3f350000,0xbf35bf80}, {0x3f350000,0xbf35bf80,0x3f353f80,0x3f350000},
{0x3f80,0x3f800000,0xbf800000,0x3f80}, {0xbf80,0xbf800000,0x3f800000,0xbf80},
{0x3f80,0x3f800000,0xbf800000,0x3f80}, {0xbf80,0xbf800000,0x3f800000,0xbf80},
{0xbf353f80,0x3f350000,0xbf350000,0xbf353f80}, {0x3f350000,0x3f35bf80,0xbf353f80,0x3f350000},
{0x3f35bf80,0xbf350000,0x3f350000,0x3f35bf80}, {0xbf350000,0xbf353f80,0x3f35bf80,0xbf350000},
{0xbf803f80,0x0,0x0,0xbf803f80}, {0xbf803f80,0x0,0x0,0xbf803f80},
{0xbf803f80,0x0,0x0,0xbf803f80}, {0xbf803f80,0x0,0x0,0xbf803f80},
{0xbf353f80,0xbf350000,0x3f350000,0xbf353f80}, {0x3f350000,0xbf353f80,0x3f35bf80,0x3f350000},
{0x3f35bf80,0x3f350000,0xbf350000,0x3f35bf80}, {0xbf350000,0x3f35bf80,0xbf353f80,0xbf350000},
{0x3f80,0xbf800000,0x3f800000,0x3f80}, {0xbf80,0x3f800000,0xbf800000,0xbf80},
{0x3f80,0xbf800000,0x3f800000,0x3f80}, {0xbf80,0x3f800000,0xbf800000,0xbf80},
{0x3f353f80,0xbf350000,0x3f350000,0x3f353f80}, {0xbf350000,0xbf35bf80,0x3f353f80,0xbf350000},
{0xbf35bf80,0x3f350000,0xbf350000,0xbf35bf80}, {0x3f350000,0x3f353f80,0xbf35bf80,0x3f350000},
{0x80008000,0x80008000,0x80008000,0x80008000}, {0x80008000,0x80008000,0x80008000,0x80008000},
{0x80008000,0x80008000,0x80008000,0x80008000}, {0x80008000,0x80008000,0x80008000,0x80008000},
{0xbf808000,0xbf808000,0x3f808000,0x3f808000}, {0x3f808000,0x3f808000,0xbf808000,0xbf808000},
{0xbf808000,0xbf808000,0x3f808000,0x3f808000}, {0x3f808000,0x3f808000,0xbf808000,0xbf808000},
{0xbec48000,0x3ec48000,0x3ec48000,0xbec48000}, {0xbf6dbf35,0x3f6d3f35,0x3f6dbf35,0xbf6d3f35},
{0xbf6dbf80,0x3f6d3f80,0x3f6dbf80,0xbf6d3f80}, {0xbec4bf35,0x3ec43f35,0x3ec4bf35,0xbec43f35},
{0xbf6d8000,0x3f6d8000,0x3f6d8000,0xbf6d8000}, {0x3ec43f35,0xbec4bf35,0xbec43f35,0x3ec4bf35},
{0x3ec4bf80,0xbec43f80,0xbec4bf80,0x3ec43f80}, {0xbf6d3f35,0x3f6dbf35,0x3f6d3f35,0xbf6dbf35},
{0xbf358000,0xbf358000,0x3f358000,0x3f358000}, {0xbf35bf80,0xbf35bf80,0x3f35bf80,0x3f35bf80},
{0x3f358000,0x3f358000,0xbf358000,0xbf358000}, {0x3f353f80,0x3f353f80,0xbf353f80,0xbf353f80},
{0xbf358000,0xbf358000,0x3f358000,0x3f358000}, {0xbf353f80,0xbf353f80,0x3f353f80,0x3f353f80},
{0x3f358000,0x3f358000,0xbf358000,0xbf358000}, {0x3f35bf80,0x3f35bf80,0xbf35bf80,0xbf35bf80},
{0xbf6d8000,0x3f6d8000,0x3f6d8000,0xbf6d8000}, {0x3ec4bf35,0xbec43f35,0xbec4bf35,0x3ec43f35},
{0x3ec43f80,0xbec4bf80,0xbec43f80,0x3ec4bf80}, {0xbf6dbf35,0x3f6d3f35,0x3f6dbf35,0xbf6d3f35},
{0xbec48000,0x3ec48000,0x3ec48000,0xbec48000}, {0xbf6d3f35,0x3f6dbf35,0x3f6d3f35,0xbf6dbf35},
{0xbf6d3f80,0x3f6dbf80,0x3f6d3f80,0xbf6dbf80}, {0xbec43f35,0x3ec4bf35,0x3ec43f35,0xbec4bf35},
{0x3f80,0x3f800000,0x3f80,0x3f800000}, {0x3f80,0x3f800000,0x3f80,0x3f800000},
{0x3f80,0x3f800000,0x3f80,0x3f800000}, {0x3f80,0x3f800000,0x3f80,0x3f800000},
{0x3f80,0x3f800000,0xbec43f6d,0x3f6d3ec4}, {0xbf353f35,0x3f353f35,0xbf6d3ec4,0x3ec43f6d},
{0xbf800000,0x3f80,0xbf6dbec4,0xbec43f6d}, {0xbf35bf35,0xbf353f35,0xbec4bf6d,0xbf6d3ec4},
{0x3f80,0x3f800000,0xbf353f35,0x3f353f35}, {0xbf800000,0x3f80,0xbf35bf35,0xbf353f35},
{0xbf80,0xbf800000,0x3f35bf35,0xbf35bf35}, {0x3f800000,0xbf80,0x3f353f35,0x3f35bf35},
{0x3f80,0x3f800000,0xbf6d3ec4,0x3ec43f6d}, {0xbf35bf35,0xbf353f35,0x3ec4bf6d,0xbf6dbec4},
{0x3f800000,0xbf80,0x3ec43f6d,0x3f6dbec4}, {0xbf353f35,0x3f353f35,0xbf6dbec4,0xbec43f6d},
{0x3f80,0x3f800000,0xbf800000,0x3f80}, {0xbf80,0xbf800000,0x3f800000,0xbf80},
{0x3f80,0x3f800000,0xbf800000,0x3f80}, {0xbf80,0xbf800000,0x3f800000,0xbf80},
{0x3f80,0x3f800000,0xbf6dbec4,0xbec43f6d}, {0x3f35bf35,0xbf35bf35,0x3ec43f6d,0x3f6dbec4},
{0xbf800000,0x3f80,0x3ec4bf6d,0xbf6dbec4}, {0x3f353f35,0x3f35bf35,0xbf6d3ec4,0x3ec43f6d},
{0x3f80,0x3f800000,0xbf35bf35,0xbf353f35}, {0x3f800000,0xbf80,0xbf353f35,0x3f353f35},
{0xbf80,0xbf800000,0x3f353f35,0x3f35bf35}, {0xbf800000,0x3f80,0x3f35bf35,0xbf35bf35},
{0x3f80,0x3f800000,0xbec4bf6d,0xbf6d3ec4}, {0x3f353f35,0x3f35bf35,0xbf6dbec4,0xbec43f6d},
{0x3f800000,0xbf80,0xbf6d3ec4,0x3ec43f6d}, {0x3f35bf35,0xbf35bf35,0xbec43f6d,0x3f6d3ec4},
{0x3f80,0xbf800000,0x3f80,0xbf800000}, {0x3f80,0xbf800000,0x3f80,0xbf800000},
{0x3f80,0xbf800000,0x3f80,0xbf800000}, {0x3f80,0xbf800000,0x3f80,0xbf800000},
{0xbf80,0x3f800000,0xbec4bf6d,0x3f6dbec4}, {0xbf35bf35,0x3f35bf35,0xbf6dbec4,0x3ec4bf6d},
{0xbf800000,0xbf80,0xbf6d3ec4,0xbec4bf6d}, {0xbf353f35,0xbf35bf35,0xbec43f6d,0xbf6dbec4},
{0x3f80,0xbf800000,0x3f353f35,0xbf353f35}, {0x3f800000,0x3f80,0x3f35bf35,0x3f353f35},
{0xbf80,0x3f800000,0xbf35bf35,0x3f35bf35}, {0xbf800000,0xbf80,0xbf353f35,0xbf35bf35},
{0xbf80,0x3f800000,0xbf6dbec4,0x3ec4bf6d}, {0xbf353f35,0xbf35bf35,0x3ec43f6d,0xbf6d3ec4},
{0x3f800000,0x3f80,0x3ec4bf6d,0x3f6d3ec4}, {0xbf35bf35,0x3f35bf35,0xbf6d3ec4,0xbec4bf6d},
{0x3f80,0xbf800000,0x3f800000,0x3f80}, {0xbf80,0x3f800000,0xbf800000,0xbf80},
{0x3f80,0xbf800000,0x3f800000,0x3f80}, {0xbf80,0x3f800000,0xbf800000,0xbf80},
{0xbf80,0x3f800000,0xbf6d3ec4,0xbec4bf6d}, {0x3f353f35,0xbf353f35,0x3ec4bf6d,0x3f6d3ec4},
{0xbf800000,0xbf80,0x3ec43f6d,0xbf6d3ec4}, {0x3f35bf35,0x3f353f35,0xbf6dbec4,0x3ec4bf6d},
{0x3f80,0xbf800000,0x3f35bf35,0x3f353f35}, {0xbf800000,0xbf80,0x3f353f35,0xbf353f35},
{0xbf80,0x3f800000,0xbf353f35,0xbf35bf35}, {0x3f800000,0x3f80,0xbf35bf35,0x3f35bf35},
{0xbf80,0x3f800000,0xbec43f6d,0xbf6dbec4}, {0x3f35bf35,0x3f353f35,0xbf6d3ec4,0xbec4bf6d},
{0x3f800000,0x3f80,0xbf6dbec4,0x3ec4bf6d}, {0x3f353f35,0xbf353f35,0xbec4bf6d,0x3f6dbec4},
{0x3f80,0x3f800000,0xbf80,0xbf800000}, {0x3f80,0x3f800000,0xbf80,0xbf800000},
{0x3f80,0x3f800000,0xbf80,0xbf800000}, {0x3f80,0x3f800000,0xbf80,0xbf800000},
{0x3f80,0x3f800000,0x3ec4bf6d,0xbf6dbec4}, {0xbf353f35,0x3f353f35,0x3f6dbec4,0xbec4bf6d},
{0xbf800000,0x3f80,0x3f6d3ec4,0x3ec4bf6d}, {0xbf35bf35,0xbf353f35,0x3ec43f6d,0x3f6dbec4},
{0x3f80,0x3f800000,0x3f35bf35,0xbf35bf35}, {0xbf800000,0x3f80,0x3f353f35,0x3f35bf35},
{0xbf80,0xbf800000,0xbf353f35,0x3f353f35}, {0x3f800000,0xbf80,0xbf35bf35,0xbf353f35},
{0x3f80,0x3f800000,0x3f6dbec4,0xbec4bf6d}, {0xbf35bf35,0xbf353f35,0xbec43f6d,0x3f6d3ec4},
{0x3f800000,0xbf80,0xbec4bf6d,0xbf6d3ec4}, {0xbf353f35,0x3f353f35,0x3f6d3ec4,0x3ec4bf6d},
{0x3f80,0x3f800000,0x3f800000,0xbf80}, {0xbf80,0xbf800000,0xbf800000,0x3f80},
{0x3f80,0x3f800000,0x3f800000,0xbf80}, {0xbf80,0xbf800000,0xbf800000,0x3f80},
{0x3f80,0x3f800000,0x3f6d3ec4,0x3ec4bf6d}, {0x3f35bf35,0xbf35bf35,0xbec4bf6d,0xbf6d3ec4},
{0xbf800000,0x3f80,0xbec43f6d,0x3f6d3ec4}, {0x3f353f35,0x3f35bf35,0x3f6dbec4,0xbec4bf6d},
{0x3f80,0x3f800000,0x3f353f35,0x3f35bf35}, {0x3f800000,0xbf80,0x3f35bf35,0xbf35bf35},
{0xbf80,0xbf800000,0xbf35bf35,0xbf353f35}, {0xbf800000,0x3f80,0xbf353f35,0x3f353f35},
{0x3f80,0x3f800000,0x3ec43f6d,0x3f6dbec4}, {0x3f353f35,0x3f35bf35,0x3f6d3ec4,0x3ec4bf6d},
{0x3f800000,0xbf80,0x3f6dbec4,0xbec4bf6d}, {0x3f35bf35,0xbf35bf35,0x3ec4bf6d,0xbf6dbec4},
{0x3f80,0xbf800000,0xbf80,0x3f800000}, {0x3f80,0xbf800000,0xbf80,0x3f800000},
{0x3f80,0xbf800000,0xbf80,0x3f800000}, {0x3f80,0xbf800000,0xbf80,0x3f800000},
{0xbf80,0x3f800000,0x3ec43f6d,0xbf6d3ec4}, {0xbf35bf35,0x3f35bf35,0x3f6d3ec4,0xbec43f6d},
{0xbf800000,0xbf80,0x3f6dbec4,0x3ec43f6d}, {0xbf353f35,0xbf35bf35,0x3ec4bf6d,0x3f6d3ec4},
{0x3f80,0xbf800000,0xbf35bf35,0x3f35bf35}, {0x3f800000,0x3f80,0xbf353f35,0xbf35bf35},
{0xbf80,0x3f800000,0x3f353f35,0xbf353f35}, {0xbf800000,0xbf80,0x3f35bf35,0x3f353f35},
{0xbf80,0x3f800000,0x3f6d3ec4,0xbec43f6d}, {0xbf353f35,0xbf35bf35,0xbec4bf6d,0x3f6dbec4},
{0x3f800000,0x3f80,0xbec43f6d,0xbf6dbec4}, {0xbf35bf35,0x3f35bf35,0x3f6dbec4,0x3ec43f6d},
{0x3f80,0xbf800000,0xbf800000,0xbf80}, {0xbf80,0x3f800000,0x3f800000,0x3f80},
{0x3f80,0xbf800000,0xbf800000,0xbf80}, {0xbf80,0x3f800000,0x3f800000,0x3f80},
{0xbf80,0x3f800000,0x3f6dbec4,0x3ec43f6d}, {0x3f353f35,0xbf353f35,0xbec43f6d,0xbf6dbec4},
{0xbf800000,0xbf80,0xbec4bf6d,0x3f6dbec4}, {0x3f35bf35,0x3f353f35,0x3f6d3ec4,0xbec43f6d},
{0x3f80,0xbf800000,0xbf353f35,0xbf35bf35}, {0xbf800000,0xbf80,0xbf35bf35,0x3f35bf35},
{0xbf80,0x3f800000,0x3f35bf35,0x3f353f35}, {0x3f800000,0x3f80,0x3f353f35,0xbf353f35},
{0xbf80,0x3f800000,0x3ec4bf6d,0x3f6d3ec4}, {0x3f35bf35,0x3f353f35,0x3f6dbec4,0x3ec43f6d},
{0x3f800000,0x3f80,0x3f6d3ec4,0xbec43f6d}, {0x3f353f35,0xbf353f35,0x3ec43f6d,0xbf6d3ec4},
{0x3f80,0x3f800000,0x3f80,0x3f800000}, {0x3f80,0x3f800000,0x3f80,0x3f800000},
{0x3f80,0x3f800000,0x3f80,0x3f800000}, {0x3f80,0x3f800000,0x3f80,0x3f800000},
{0xbe483f7b,0x3f7b3e48,0xbf0e3f55,0x3f553f0e}, {0xbf553f0e,0x3f0e3f55,0xbf7b3e48,0x3e483f7b},
{0xbf7bbe48,0xbe483f7b,0xbf55bf0e,0xbf0e3f55}, {0xbf0ebf55,0xbf553f0e,0xbe48bf7b,0xbf7b3e48},
{0xbec43f6d,0x3f6d3ec4,0xbf6d3ec4,0x3ec43f6d}, {0xbf6dbec4,0xbec43f6d,0xbec4bf6d,0xbf6d3ec4},
{0x3ec4bf6d,0xbf6dbec4,0x3f6dbec4,0xbec4bf6d}, {0x3f6d3ec4,0x3ec4bf6d,0x3ec43f6d,0x3f6dbec4},
{0xbf0e3f55,0x3f553f0e,0xbf7bbe48,0xbe483f7b}, {0xbe48bf7b,0xbf7b3e48,0x3f55bf0e,0xbf0ebf55},
{0x3f553f0e,0x3f0ebf55,0xbe483f7b,0x3f7b3e48}, {0xbf7b3e48,0x3e483f7b,0xbf0ebf55,0xbf553f0e},
{0xbf353f35,0x3f353f35,0xbf35bf35,0xbf353f35}, {0x3f35bf35,0xbf35bf35,0x3f353f35,0x3f35bf35},
{0xbf353f35,0x3f353f35,0xbf35bf35,0xbf353f35}, {0x3f35bf35,0xbf35bf35,0x3f353f35,0x3f35bf35},
{0xbf553f0e,0x3f0e3f55,0xbe48bf7b,0xbf7b3e48}, {0x3f7b3e48,0x3e48bf7b,0xbf0e3f55,0x3f553f0e},
{0xbf0ebf55,0xbf553f0e,0x3f7bbe48,0xbe48bf7b}, {0xbe483f7b,0x3f7b3e48,0xbf55bf0e,0xbf0e3f55},
{0xbf6d3ec4,0x3ec43f6d,0x3ec4bf6d,0xbf6dbec4}, {0x3ec43f6d,0x3f6dbec4,0xbf6dbec4,0xbec43f6d},
{0x3f6dbec4,0xbec4bf6d,0xbec43f6d,0x3f6d3ec4}, {0xbec4bf6d,0xbf6d3ec4,0x3f6d3ec4,0x3ec4bf6d},
{0xbf7b3e48,0x3e483f7b,0x3f55bf0e,0xbf0ebf55}, {0xbf0e3f55,0x3f553f0e,0x3e48bf7b,0xbf7bbe48},
{0x3e483f7b,0x3f7bbe48,0xbf0ebf55,0xbf553f0e}, {0x3f553f0e,0x3f0ebf55,0xbf7bbe48,0xbe483f7b},
{0x3f80,0xbf800000,0x3f80,0xbf800000}, {0x3f80,0xbf800000,0x3f80,0xbf800000},
{0x3f80,0xbf800000,0x3f80,0xbf800000}, {0x3f80,0xbf800000,0x3f80,0xbf800000},
{0xbe48bf7b,0x3f7bbe48,0xbf0ebf55,0x3f55bf0e}, {0xbf55bf0e,0x3f0ebf55,0xbf7bbe48,0x3e48bf7b},
{0xbf7b3e48,0xbe48bf7b,0xbf553f0e,0xbf0ebf55}, {0xbf0e3f55,0xbf55bf0e,0xbe483f7b,0xbf7bbe48},
{0x3ec43f6d,0xbf6d3ec4,0x3f6d3ec4,0xbec43f6d}, {0x3f6dbec4,0x3ec43f6d,0x3ec4bf6d,0x3f6d3ec4},
{0xbec4bf6d,0x3f6dbec4,0xbf6dbec4,0x3ec4bf6d}, {0xbf6d3ec4,0xbec4bf6d,0xbec43f6d,0xbf6dbec4},
{0xbf0ebf55,0x3f55bf0e,0xbf7b3e48,0xbe48bf7b}, {0xbe483f7b,0xbf7bbe48,0x3f553f0e,0xbf0e3f55},
{0x3f55bf0e,0x3f0e3f55,0xbe48bf7b,0x3f7bbe48}, {0xbf7bbe48,0x3e48bf7b,0xbf0e3f55,0xbf55bf0e},
{0x3f353f35,0xbf353f35,0x3f35bf35,0x3f353f35}, {0xbf35bf35,0x3f35bf35,0xbf353f35,0xbf35bf35},
{0x3f353f35,0xbf353f35,0x3f35bf35,0x3f353f35}, {0xbf35bf35,0x3f35bf35,0xbf353f35,0xbf35bf35},
{0xbf55bf0e,0x3f0ebf55,0xbe483f7b,0xbf7bbe48}, {0x3f7bbe48,0x3e483f7b,0xbf0ebf55,0x3f55bf0e},
{0xbf0e3f55,0xbf55bf0e,0x3f7b3e48,0xbe483f7b}, {0xbe48bf7b,0x3f7bbe48,0xbf553f0e,0xbf0ebf55},
{0x3f6d3ec4,0xbec43f6d,0xbec4bf6d,0x3f6dbec4}, {0xbec43f6d,0xbf6dbec4,0x3f6dbec4,0x3ec43f6d},
{0xbf6dbec4,0x3ec4bf6d,0x3ec43f6d,0xbf6d3ec4}, {0x3ec4bf6d,0x3f6d3ec4,0xbf6d3ec4,0xbec4bf6d},
{0xbf7bbe48,0x3e48bf7b,0x3f553f0e,0xbf0e3f55}, {0xbf0ebf55,0x3f55bf0e,0x3e483f7b,0xbf7b3e48},
{0x3e48bf7b,0x3f7b3e48,0xbf0e3f55,0xbf55bf0e}, {0x3f55bf0e,0x3f0e3f55,0xbf7b3e48,0xbe48bf7b},
{0xbf800000,0x3f80,0x3f800000,0xbf80}, {0xbf800000,0x3f80,0x3f800000,0xbf80},
{0xbf800000,0x3f80,0x3f800000,0xbf80}, {0xbf800000,0x3f80,0x3f800000,0xbf80},
{0xbf7bbe48,0xbe483f7b,0x3f553f0e,0x3f0ebf55}, {0xbf0ebf55,0xbf553f0e,0x3e483f7b,0x3f7bbe48},
{0x3e48bf7b,0xbf7bbe48,0xbf0e3f55,0x3f553f0e}, {0x3f55bf0e,0xbf0ebf55,0xbf7b3e48,0x3e483f7b},
{0xbf6dbec4,0xbec43f6d,0x3ec43f6d,0x3f6dbec4}, {0x3ec4bf6d,0xbf6dbec4,0xbf6d3ec4,0x3ec43f6d},
{0x3f6d3ec4,0x3ec4bf6d,0xbec4bf6d,0xbf6d3ec4}, {0xbec43f6d,0x3f6d3ec4,0x3f6dbec4,0xbec4bf6d},
{0xbf55bf0e,0xbf0e3f55,0xbe483f7b,0x3f7b3e48}, {0x3f7bbe48,0xbe48bf7b,0xbf0ebf55,0xbf553f0e},
{0xbf0e3f55,0x3f553f0e,0x3f7b3e48,0x3e48bf7b}, {0xbe48bf7b,0xbf7b3e48,0xbf553f0e,0x3f0e3f55},
{0xbf35bf35,0xbf353f35,0xbf353f35,0x3f353f35}, {0x3f353f35,0x3f35bf35,0x3f35bf35,0xbf35bf35},
{0xbf35bf35,0xbf353f35,0xbf353f35,0x3f353f35}, {0x3f353f35,0x3f35bf35,0x3f35bf35,0xbf35bf35},
{0xbf0ebf55,0xbf553f0e,0xbf7b3e48,0x3e483f7b}, {0xbe483f7b,0x3f7b3e48,0x3f553f0e,0x3f0ebf55},
{0x3f55bf0e,0xbf0ebf55,0xbe48bf7b,0xbf7b3e48}, {0xbf7bbe48,0xbe483f7b,0xbf0e3f55,0x3f553f0e},
{0xbec4bf6d,0xbf6d3ec4,0xbf6dbec4,0xbec43f6d}, {0xbf6d3ec4,0x3ec43f6d,0xbec43f6d,0x3f6d3ec4},
{0x3ec43f6d,0x3f6dbec4,0x3f6d3ec4,0x3ec4bf6d}, {0x3f6dbec4,0xbec4bf6d,0x3ec4bf6d,0xbf6dbec4},
{0xbe48bf7b,0xbf7b3e48,0xbf0ebf55,0xbf553f0e}, {0xbf55bf0e,0xbf0e3f55,0xbf7bbe48,0xbe483f7b},
{0xbf7b3e48,0x3e483f7b,0xbf553f0e,0x3f0e3f55}, {0xbf0e3f55,0x3f553f0e,0xbe483f7b,0x3f7b3e48},
{0x3f800000,0x3f80,0xbf800000,0xbf80}, {0x3f800000,0x3f80,0xbf800000,0xbf80},
{0x3f800000,0x3f80,0xbf800000,0xbf80}, {0x3f800000,0x3f80,0xbf800000,0xbf80},
{0xbf7b3e48,0xbe48bf7b,0x3f55bf0e,0x3f0e3f55}, {0xbf0e3f55,0xbf55bf0e,0x3e48bf7b,0x3f7b3e48},
{0x3e483f7b,0xbf7b3e48,0xbf0ebf55,0x3f55bf0e}, {0x3f553f0e,0xbf0e3f55,0xbf7bbe48,0x3e48bf7b},
{0x3f6dbec4,0x3ec43f6d,0xbec43f6d,0xbf6dbec4}, {0xbec4bf6d,0x3f6dbec4,0x3f6d3ec4,0xbec43f6d},
{0xbf6d3ec4,0xbec4bf6d,0x3ec4bf6d,0x3f6d3ec4}, {0x3ec43f6d,0xbf6d3ec4,0xbf6dbec4,0x3ec4bf6d},
{0xbf553f0e,0xbf0ebf55,0xbe48bf7b,0x3f7bbe48}, {0x3f7b3e48,0xbe483f7b,0xbf0e3f55,0xbf55bf0e},
{0xbf0ebf55,0x3f55bf0e,0x3f7bbe48,0x3e483f7b}, {0xbe483f7b,0xbf7bbe48,0xbf55bf0e,0x3f0ebf55},
{0x3f35bf35,0x3f353f35,0x3f353f35,0xbf353f35}, {0xbf353f35,0xbf35bf35,0xbf35bf35,0x3f35bf35},
{0x3f35bf35,0x3f353f35,0x3f353f35,0xbf353f35}, {0xbf353f35,0xbf35bf35,0xbf35bf35,0x3f35bf35},
{0xbf0e3f55,0xbf55bf0e,0xbf7bbe48,0x3e48bf7b}, {0xbe48bf7b,0x3f7bbe48,0x3f55bf0e,0x3f0e3f55},
{0x3f553f0e,0xbf0e3f55,0xbe483f7b,0xbf7bbe48}, {0xbf7b3e48,0xbe48bf7b,0xbf0ebf55,0x3f55bf0e},
{0x3ec4bf6d,0x3f6d3ec4,0x3f6dbec4,0x3ec43f6d}, {0x3f6d3ec4,0xbec43f6d,0x3ec43f6d,0xbf6d3ec4},
{0xbec43f6d,0xbf6dbec4,0xbf6d3ec4,0xbec4bf6d}, {0xbf6dbec4,0x3ec4bf6d,0xbec4bf6d,0x3f6dbec4},
{0xbe483f7b,0xbf7bbe48,0xbf0e3f55,0xbf55bf0e}, {0xbf553f0e,0xbf0ebf55,0xbf7b3e48,0xbe48bf7b},
{0xbf7bbe48,0x3e48bf7b,0xbf55bf0e,0x3f0ebf55}, {0xbf0ebf55,0x3f55bf0e,0xbe48bf7b,0x3f7bbe48},
{0x3f800000,0x0,0x3f800000,0x0}, {0x3f800000,0x0,0x3f800000,0x0},
{0x3f800000,0x0,0x3f800000,0x0}, {0x3f800000,0x0,0x3f800000,0x0},
{0x3f800000,0x0,0x3f7ff98e,0x3c65c70c}, {0x3f7fe638,0x3ce5c143,0x3f7fc600,0x3d2c49b7},
{0x3f7f98e6,0x3d65aa20,0x3f7f5eee,0x3d8f7f7c}, {0x3f7f181a,0x3dac22ae,0x3f7ec46d,0x3dc8bd36},
{0x3f800000,0x0,0x3f7fe638,0x3ce5c143}, {0x3f7f98e6,0x3d65aa20,0x3f7f181a,0x3dac22ae},
{0x3f7e63ec,0x3de54da2,0x3f7d7c83,0x3e0f2533}, {0x3f7c620b,0x3e2b86c0,0x3f7b14be,0x3e47c5c2},
{0x3f800000,0x0,0x3f7fc600,0x3d2c49b7}, {0x3f7f181a,0x3dac22ae,0x3f7df69c,0x3e00e941},
{0x3f7c620b,0x3e2b86c0,0x3f7a5b1d,0x3e55d687}, {0x3f77e2bd,0x3e7fc568,0x3f74fa0b,0x3e94a031},
{0x3f800000,0x0,0x3f7f98e6,0x3d65aa20}, {0x3f7e63ec,0x3de54da2,0x3f7c620b,0x3e2b86c0},
{0x3f7994e0,0x3e63dc87,0x3f75fead,0x3e8dbd62}, {0x3f71a257,0x3ea91a56,0x3f6c835e,0x3ec3ef15},
{0x3f800000,0x0,0x3f7f5eee,0x3d8f7f7c}, {0x3f7d7c83,0x3e0f2533,0x3f7a5b1d,0x3e55d687},
{0x3f75fead,0x3e8dbd62,0x3f706cb1,0x3eafdd25}, {0x3f69ac2a,0x3ed11f9b,0x3f61c598,0x3ef15aea},
{0x3f800000,0x0,0x3f7f181a,0x3dac22ae}, {0x3f7c620b,0x3e2b86c0,0x3f77e2bd,0x3e7fc568},
{0x3f71a257,0x3ea91a56,0x3f69ac2a,0x3ed11f9b}, {0x3f600ea4,0x3ef7aa01,0x3f54db31,0x3f0e39da},
{0x3f800000,0x0,0x3f7ec46d,0x3dc8bd36}, {0x3f7b14be,0x3e47c5c2,0x3f74fa0b,0x3e94a031},
{0x3f6c835e,0x3ec3ef15,0x3f61c598,0x3ef15aea}, {0x3f54db31,0x3f0e39da,0x3f45e403,0x3f226799},
{0x3f800000,0x0,0x3f7e63ec,0x3de54da2}, {0x3f7994e0,0x3e63dc87,0x3f71a257,0x3ea91a56},
{0x3f66a5e5,0x3ede2602,0x3f58c2eb,0x3f083341}, {0x3f48261c,0x3f1f9d07,0x3f3504f3,0x3f3504f3},
{0x3f800000,0x0,0x3f7df69c,0x3e00e941}, {0x3f77e2bd,0x3e7fc568,0x3f6ddd24,0x3ebd47db},
{0x3f600ea4,0x3ef7aa01,0x3f4eaf7a,0x3f170daa}, {0x3f3a0669,0x3f2fdf08,0x3f226799,0x3f45e403},
{0x3f800000,0x0,0x3f7d7c83,0x3e0f2533}, {0x3f75fead,0x3e8dbd62,0x3f69ac2a,0x3ed11f9b},
{0x3f58c2eb,0x3f083341,0x3f4397f4,0x3f2529fe}, {0x3f2a95b0,0x3f3ee268,0x3f0e39da,0x3f54db31},
{0x3f800000,0x0,0x3f7cf5a5,0x3e1d59f0}, {0x3f73e912,0x3e9b7b85,0x3f65114d,0x3ee49898},
{0x3f50c899,0x3f1423cd,0x3f378a4d,0x3f32767c}, {0x3f19efeb,0x3f4c8bf3,0x3ef15aea,0x3f61c598},
{0x3f800000,0x0,0x3f7c620b,0x3e2b86c0}, {0x3f71a257,0x3ea91a56,0x3f600ea4,0x3ef7aa01},
{0x3f48261c,0x3f1f9d07,0x3f2a95b0,0x3f3ee268}, {0x3f083341,0x3f58c2eb,0x3ec3ef15,0x3f6c835e},
{0x3f800000,0x0,0x3f7bc1bb,0x3e39aaee}, {0x3f6f2af0,0x3eb69719,0x3f5aa675,0x3f052598},
{0x3f3ee268,0x3f2a95b0,0x3f1cca6b,0x3f4a5e20}, {0x3eeaffac,0x3f63712c,0x3e94a031,0x3f74fa0b},
{0x3f800000,0x0,0x3f7b14be,0x3e47c5c2}, {0x3f6c835e,0x3ec3ef15,0x3f54db31,0x3f0e39da},
{0x3f3504f3,0x3f3504f3,0x3f0e39da,0x3f54db31}, {0x3ec3ef15,0x3f6c835e,0x3e47c5c2,0x3f7b14be},
{0x3f800000,0x0,0x3f7a5b1d,0x3e55d687}, {0x3f69ac2a,0x3ed11f9b,0x3f4eaf7a,0x3f170daa},
{0x3f2a95b0,0x3f3ee268,0x3efdec9f,0x3f5e4c69}, {0x3e9b7b85,0x3f73e912,0x3dc8bd36,0x3f7ec46d},
{0x3f800000,0x0,0x3f7994e0,0x3e63dc87}, {0x3f66a5e5,0x3ede2602,0x3f48261c,0x3f1f9d07},
{0x3f1f9d07,0x3f48261c,0x3ede2602,0x3f66a5e5}, {0x3e63dc87,0x3f7994e0,0x0,0x3f800000},
{0x3f800000,0x0,0x3f78c212,0x3e71d70e}, {0x3f63712c,0x3eeaffac,0x3f41420b,0x3f27e411},
{0x3f1423cd,0x3f50c899,0x3ebd47db,0x3f6ddd24}, {0x3e0f2533,0x3f7d7c83,0xbdc8bd36,0x3f7ec46d},
{0x3f800000,0x0,0x3f77e2bd,0x3e7fc568}, {0x3f600ea4,0x3ef7aa01,0x3f3a0669,0x3f2fdf08},
{0x3f083341,0x3f58c2eb,0x3e9b7b85,0x3f73e912}, {0x3d65aa20,0x3f7f98e6,0xbe47c5c2,0x3f7b14be},
{0x3f800000,0x0,0x3f76f6ed,0x3e86d370}, {0x3f5c7efc,0x3f02113a,0x3f32767c,0x3f378a4d},
{0x3ef7aa01,0x3f600ea4,0x3e71d70e,0x3f78c212}, {0xbce5c143,0x3f7fe638,0xbe94a031,0x3f74fa0b},
{0x3f800000,0x0,0x3f75fead,0x3e8dbd62}, {0x3f58c2eb,0x3f083341,0x3f2a95b0,0x3f3ee268},
{0x3ede2602,0x3f66a5e5,0x3e2b86c0,0x3f7c620b}, {0xbde54da2,0x3f7e63ec,0xbec3ef15,0x3f6c835e},
{0x3f800000,0x0,0x3f74fa0b,0x3e94a031}, {0x3f54db31,0x3f0e39da,0x3f226799,0x3f45e403},
{0x3ec3ef15,0x3f6c835e,0x3dc8bd36,0x3f7ec46d}, {0xbe47c5c2,0x3f7b14be,0xbef15aea,0x3f61c598},
{0x3f800000,0x0,0x3f73e912,0x3e9b7b85}, {0x3f50c899,0x3f1423cd,0x3f19efeb,0x3f4c8bf3},
{0x3ea91a56,0x3f71a257,0x3ce5c143,0x3f7fe638}, {0xbe8dbd62,0x3f75fead,0xbf0e39da,0x3f54db31},
{0x3f800000,0x0,0x3f72cbd1,0x3ea24f04}, {0x3f4c8bf3,0x3f19efeb,0x3f11327b,0x3f52d734},
{0x3e8dbd62,0x3f75fead,0xbd2c49b7,0x3f7fc600}, {0xbeb69719,0x3f6f2af0,0xbf226799,0x3f45e403},
{0x3f800000,0x0,0x3f71a257,0x3ea91a56}, {0x3f48261c,0x3f1f9d07,0x3f083341,0x3f58c2eb},
{0x3e63dc87,0x3f7994e0,0xbde54da2,0x3f7e63ec}, {0xbede2602,0x3f66a5e5,0xbf3504f3,0x3f3504f3},
{0x3f800000,0x0,0x3f706cb1,0x3eafdd25}, {0x3f4397f4,0x3f2529fe,0x3efdec9f,0x3f5e4c69},
{0x3e2b86c0,0x3f7c620b,0xbe39aaee,0x3f7bc1bb}, {0xbf02113a,0x3f5c7efc,0xbf45e403,0x3f226799},
{0x3f800000,0x0,0x3f6f2af0,0x3eb69719}, {0x3f3ee268,0x3f2a95b0,0x3eeaffac,0x3f63712c},
{0x3de54da2,0x3f7e63ec,0xbe7fc568,0x3f77e2bd}, {0xbf1423cd,0x3f50c899,0xbf54db31,0x3f0e39da},
{0x3f800000,0x0,0x3f6ddd24,0x3ebd47db}, {0x3f3a0669,0x3f2fdf08,0x3ed7a83d,0x3f682ee0},
{0x3d65aa20,0x3f7f98e6,0xbea24f04,0x3f72cbd1}, {0xbf2529fe,0x3f4397f4,0xbf61c598,0x3ef15aea},
{0x3f800000,0x0,0x3f6c835e,0x3ec3ef15}, {0x3f3504f3,0x3f3504f3,0x3ec3ef15,0x3f6c835e},
{0x0,0x3f800000,0xbec3ef15,0x3f6c835e}, {0xbf3504f3,0x3f3504f3,0xbf6c835e,0x3ec3ef15},
{0x3f800000,0x0,0x3f6b1db0,0x3eca8c72}, {0x3f2fdf08,0x3f3a0669,0x3eafdd25,0x3f706cb1},
{0xbd65aa20,0x3f7f98e6,0xbee49898,0x3f65114d}, {0xbf4397f4,0x3f2529fe,0xbf74fa0b,0x3e94a031},
{0x3f800000,0x0,0x3f69ac2a,0x3ed11f9b}, {0x3f2a95b0,0x3f3ee268,0x3e9b7b85,0x3f73e912},
{0xbde54da2,0x3f7e63ec,0xbf02113a,0x3f5c7efc}, {0xbf50c899,0x3f1423cd,0xbf7b14be,0x3e47c5c2},
{0x3f800000,0x0,0x3f682ee0,0x3ed7a83d}, {0x3f2529fe,0x3f4397f4,0x3e86d370,0x3f76f6ed},
{0xbe2b86c0,0x3f7c620b,0xbf11327b,0x3f52d734}, {0xbf5c7efc,0x3f02113a,0xbf7ec46d,0x3dc8bd36},
{0x40003f80,0xbfe73f80,0x0,0x3f5e0000}, {0x40004000,0xbee43fa0,0x0,0x3ffabfc8},
{0x40004000,0x3fa0bee4,0x0,0x3fc8bffa}, {0x3f804000,0x3f80bfe7,0x0,0xbf5e},
{0x3fe73f80,0xbfa03f80,0xbf5e0000,0x3fc80000}, {0x3ee43fa0,0x3fe7bee4,0xbffabfc8,0x3f5ebffa},
{0xbfa0bee4,0x3ee4bfe7,0xbfc8bffa,0xbffa3f5e}, {0xbf80bfe7,0xbf803fa0,0xbf5e,0x3fc8},
{0x3fa03f80,0xbee43f80,0xbfc80000,0x3ffa0000}, {0xbfe7bee4,0x3fa0bfe7,0xbf5ebffa,0xbfc8bf5e},
{0xbee4bfe7,0xbfe73fa0,0x3ffa3f5e,0x3f5e3fc8}, {0x3f803fa0,0x3f80bee4,0x3fc8,0xbffa},
{0x3ee43f80,0x3ee43f80,0xbffa0000,0x3ffa0000}, {0xbfa0bfe7,0xbfa0bfe7,0x3fc8bf5e,0xbfc83f5e},
{0x3fe73fa0,0x3fe73fa0,0xbf5e3fc8,0x3f5ebfc8}, {0xbf80bee4,0xbf80bee4,0xbffa,0x3ffa},
{0xbee43f80,0x3fa03f80,0xbffa0000,0x3fc80000}, {0x3fa0bfe7,0xbfe7bee4,0x3fc83f5e,0x3f5e3ffa},
{0xbfe73fa0,0xbee4bfe7,0xbf5ebfc8,0xbffabf5e}, {0x3f80bee4,0x3f803fa0,0x3ffa,0xbfc8},
{0xbfa03f80,0x3fe73f80,0xbfc80000,0x3f5e0000}, {0x3fe7bee4,0x3ee43fa0,0xbf5e3ffa,0x3ffa3fc8},
{0x3ee4bfe7,0xbfa0bee4,0x3ffabf5e,0x3fc83ffa}, {0xbf803fa0,0xbf80bfe7,0xbfc8,0x3f5e},
{0xbfe73f80,0x0,0xbf5e0000,0x0}, {0xbee43fa0,0x0,0xbffa3fc8,0x0},
{0x3fa0bee4,0x0,0xbfc83ffa,0x0}, {0x3f80bfe7,0x0,0x3f5e,0x0},
{0xc0003f80,0x0,0x0,0x0}, {0xc0004000,0x0,0x0,0x0},
{0xc0004000,0x0,0x0,0x0}, {0xbf804000,0x0,0x0,0x0},
};


struct Scratch {
    uint4 S1[128 * 1024];
    uint4 S2[128 * 1024];
    uint4 hp[32 * 4 * 896];
    uint4 h[2048 * 56];
    uint4 u[28 * 4 * 896];
    unsigned sync[288];
};
__device__ __align__(1024) Scratch g_scr;

__device__ __forceinline__ uint32_t s2u(const void* p) { return (uint32_t)__cvta_generic_to_shared(p); }
__device__ __forceinline__ void mbar_init(uint32_t b, int c) { asm volatile("mbarrier.init.shared::cta.b64 [%0], %1;" :: "r"(b), "r"(c) : "memory"); }
__device__ __forceinline__ void mbar_expect(uint32_t b, int bytes) { asm volatile("mbarrier.arrive.expect_tx.shared::cta.b64 _, [%0], %1;" :: "r"(b), "r"(bytes) : "memory"); }
__device__ __forceinline__ void mbar_arrive(uint32_t b) { asm volatile("mbarrier.arrive.shared::cta.b64 _, [%0];" :: "r"(b) : "memory"); }
__device__ __forceinline__ void arrive_remote(uint32_t b, uint32_t cta) {
    asm volatile("{\n.reg .b32 ra;\nmapa.shared::cluster.u32 ra, %0, %1;\nmbarrier.arrive.shared::cluster.b64 _, [ra];\n}\n" :: "r"(b), "r"(cta) : "memory");
}
__device__ __forceinline__ void mbar_wait0(uint32_t b) {
    asm volatile("{\n.reg .pred p, q;\n.reg .u32 c;\n"
                 "mbarrier.try_wait.parity.shared::cta.b64 p, [%0], 0;\n@p bra.uni D_%=;\nmov.u32 c, 0;\n"
                 "W_%=:\nmbarrier.try_wait.parity.shared::cta.b64 p, [%0], 0;\n@p bra.uni D_%=;\n"
                 "add.u32 c, c, 1;\nsetp.lt.u32 q, c, 20000;\n@q bra.uni W_%=;\nD_%=:\n}\n" :: "r"(b) : "memory");
}
__device__ __forceinline__ void bulk_load_e(uint32_t dst, const void* src, int bytes, uint32_t bar) {
    asm volatile("{\n.reg .pred p;\nelect.sync _|p, 0xffffffff;\n@p cp.async.bulk.shared::cluster.global.mbarrier::complete_tx::bytes [%0], [%1], %2, [%3];\n}\n" :: "r"(dst), "l"(src), "r"(bytes), "r"(bar) : "memory");
}
__device__ __forceinline__ void bulk_store_e(void* dst, uint32_t src, int bytes) {
    asm volatile("{\n.reg .pred p;\nelect.sync _|p, 0xffffffff;\n@p cp.async.bulk.global.shared::cta.bulk_group [%0], [%1], %2;\n}\n" :: "l"(dst), "r"(src), "r"(bytes) : "memory");
}
__device__ __forceinline__ void tma2d_e(uint32_t dst, const CUtensorMap* m, int c0, int c1, uint32_t bar) {
    asm volatile("{\n.reg .pred p;\nelect.sync _|p, 0xffffffff;\n@p cp.async.bulk.tensor.2d.shared::cluster.global.mbarrier::complete_tx::bytes [%0], [%1, {%2, %3}], [%4];\n}\n" :: "r"(dst), "l"(m), "r"(c0), "r"(c1), "r"(bar) : "memory");
}
__device__ __forceinline__ void tma2d_mc_e(uint32_t dst, const CUtensorMap* m, int c0, int c1, uint32_t bar) {
    asm volatile("{\n.reg .pred p;\nelect.sync _|p, 0xffffffff;\n@p cp.async.bulk.tensor.2d.shared::cluster.global.mbarrier::complete_tx::bytes.multicast::cluster [%0], [%1, {%2, %3}], [%4], %5;\n}\n" :: "r"(dst), "l"(m), "r"(c0), "r"(c1), "r"(bar), "h"((uint16_t)3) : "memory");
}
__device__ __forceinline__ void tma3d_mc_e(uint32_t dst, const CUtensorMap* m, int c0, int c1, int c2, uint32_t bar) {
    asm volatile("{\n.reg .pred p;\nelect.sync _|p, 0xffffffff;\n@p cp.async.bulk.tensor.3d.shared::cluster.global.mbarrier::complete_tx::bytes.multicast::cluster [%0], [%1, {%2, %3, %4}], [%5], %6;\n}\n" :: "r"(dst), "l"(m), "r"(c0), "r"(c1), "r"(c2), "r"(bar), "h"((uint16_t)3) : "memory");
}
__device__ __forceinline__ void pf2d_e(const CUtensorMap* m, int c0, int c1) {
    asm volatile("{\n.reg .pred p;\nelect.sync _|p, 0xffffffff;\n@p cp.async.bulk.prefetch.tensor.2d.L2.global [%0, {%1, %2}];\n}\n" :: "l"(m), "r"(c0), "r"(c1) : "memory");
}
__device__ __forceinline__ void pf3d_e(const CUtensorMap* m, int c0, int c1, int c2) {
    asm volatile("{\n.reg .pred p;\nelect.sync _|p, 0xffffffff;\n@p cp.async.bulk.prefetch.tensor.3d.L2.global [%0, {%1, %2, %3}];\n}\n" :: "l"(m), "r"(c0), "r"(c1), "r"(c2) : "memory");
}
__device__ __forceinline__ unsigned ld_relaxed(const unsigned* p) { unsigned x; asm volatile("ld.relaxed.gpu.global.u32 %0, [%1];" : "=r"(x) : "l"(p) : "memory"); return x; }
__device__ __forceinline__ unsigned ld_acquire(const unsigned* p) { unsigned x; asm volatile("ld.acquire.gpu.global.u32 %0, [%1];" : "=r"(x) : "l"(p) : "memory"); return x; }
__device__ __forceinline__ void red_release(unsigned* p) { asm volatile("red.release.gpu.global.add.u32 [%0], 1;" :: "l"(p) : "memory"); }
__device__ __forceinline__ void red_relaxed(unsigned* p) { asm volatile("red.relaxed.gpu.global.add.u32 [%0], 1;" :: "l"(p) : "memory"); }
__device__ __forceinline__ void fence_async_g() { asm volatile("fence.proxy.async.global;" ::: "memory"); }
__device__ __forceinline__ void fence_async_s() { asm volatile("fence.proxy.async.shared::cta;" ::: "memory"); }
__device__ __forceinline__ void csync() { asm volatile("bar.sync 1, 256;" ::: "memory"); }
__device__ __forceinline__ uint32_t clk32() { uint32_t c; asm volatile("mov.u32 %0, %%clock;" : "=r"(c)); return c; }

__device__ __forceinline__ uint32_t pk(float lo, float hi) { uint32_t r; asm("cvt.rn.bf16x2.f32 %0, %1, %2;" : "=r"(r) : "f"(hi), "f"(lo)); return r; }
__device__ __forceinline__ float blo(uint32_t w) { return __uint_as_float(w << 16); }
__device__ __forceinline__ float bhi(uint32_t w) { return __uint_as_float(w & 0xffff0000u); }
__device__ __forceinline__ uint32_t neg2(uint32_t w) { return w ^ 0x80008000u; }
__device__ __forceinline__ uint32_t hsub2(uint32_t a, uint32_t b) { uint32_t r; asm("sub.rn.bf16x2 %0, %1, %2;" : "=r"(r) : "r"(a), "r"(b)); return r; }
__device__ __forceinline__ uint32_t hadd2(uint32_t a, uint32_t b) { uint32_t r; asm("add.rn.bf16x2 %0, %1, %2;" : "=r"(r) : "r"(a), "r"(b)); return r; }
__device__ __forceinline__ uint32_t tagw(uint32_t w, uint32_t tag) { uint32_t r; asm("lop3.b32 %0, %1, %2, 1, 0xD8;" : "=r"(r) : "r"(w), "r"(tag)); return r; }
template <int OFF> __device__ __forceinline__ void stg4p(const void* p, bool ok, uint32_t x, uint32_t y, uint32_t z, uint32_t w) {
    asm volatile("{\n.reg .pred p;\nsetp.ne.u32 p, %5, 0;\n@p st.global.v4.u32 [%0+%6], {%1,%2,%3,%4};\n}\n" :: "l"(p), "r"(x), "r"(y), "r"(z), "r"(w), "r"((uint32_t)ok), "n"(OFF) : "memory");
}
__device__ __forceinline__ void sts4p(uint32_t a, bool ok, uint32_t x, uint32_t y, uint32_t z, uint32_t w) {
    asm volatile("{\n.reg .pred p;\nsetp.ne.u32 p, %5, 0;\n@p st.shared.v4.u32 [%0], {%1,%2,%3,%4};\n}\n" :: "r"(a), "r"(x), "r"(y), "r"(z), "r"(w), "r"((uint32_t)ok) : "memory");
}
__device__ __forceinline__ void sts2(uint32_t a, uint32_t x, uint32_t y) { asm volatile("st.shared.v2.u32 [%0], {%1,%2};" :: "r"(a), "r"(x), "r"(y) : "memory"); }
__device__ __forceinline__ uint32_t keep(uint32_t v) { return __shfl_sync(~0u, v, threadIdx.x & 31); }
template <class T> __device__ __forceinline__ T* keep(T* p) { uint64_t a = (uint64_t)p; return (T*)(((uint64_t)keep((uint32_t)(a >> 32)) << 32) | keep((uint32_t)a)); }
__device__ __forceinline__ void cs448(int j, float& c, float& s) { float a = (float)j * 1.4024967203525863e-2f; c = __cosf(a); s = __sinf(a); }
__device__ __forceinline__ float rsq(float v) { float r; asm("rsqrt.approx.ftz.f32 %0, %1;" : "=f"(r) : "f"(v)); return r; }
__device__ __forceinline__ uint4 lds4(uint32_t a) { uint4 v; asm volatile("ld.shared.v4.u32 {%0,%1,%2,%3}, [%4];" : "=r"(v.x), "=r"(v.y), "=r"(v.z), "=r"(v.w) : "r"(a) : "memory"); return v; }
__device__ __forceinline__ uint32_t lds1(uint32_t a) { uint32_t v; asm volatile("ld.shared.u32 %0, [%1];" : "=r"(v) : "r"(a) : "memory"); return v; }
__device__ __forceinline__ void sts4(uint32_t a, uint32_t x, uint32_t y, uint32_t z, uint32_t w) { asm volatile("st.shared.v4.u32 [%0], {%1,%2,%3,%4};" :: "r"(a), "r"(x), "r"(y), "r"(z), "r"(w) : "memory"); }
template <int N> __device__ __forceinline__ void ldtab_s(uint32_t (&r)[N], uint32_t a) {
#pragma unroll
    for (int i = 0; i < N / 4; i++)
        asm volatile("ld.volatile.shared.v4.u32 {%0,%1,%2,%3}, [%4];" : "=r"(r[4 * i]), "=r"(r[4 * i + 1]), "=r"(r[4 * i + 2]), "=r"(r[4 * i + 3]) : "r"(a + i * 512) : "memory");
}
__device__ __forceinline__ void spin_until(uint32_t t0, uint32_t dt) { while (clk32() - t0 < dt) {} }
__device__ __forceinline__ void mma(float (&c)[4], uint32_t a0, uint32_t a1, uint32_t a2, uint32_t a3, uint32_t b0, uint32_t b1) {
    asm("mma.sync.aligned.m16n8k16.row.col.f32.bf16.bf16.f32 {%0,%1,%2,%3}, {%4,%5,%6,%7}, {%8,%9}, {%0,%1,%2,%3};"
        : "+f"(c[0]), "+f"(c[1]), "+f"(c[2]), "+f"(c[3]) : "r"(a0), "r"(a1), "r"(a2), "r"(a3), "r"(b0), "r"(b1));
}
__device__ __forceinline__ void mma0(float (&c)[4], uint32_t a0, uint32_t a1, uint32_t a2, uint32_t a3, uint32_t b0, uint32_t b1) {
    asm("mma.sync.aligned.m16n8k16.row.col.f32.bf16.bf16.f32 {%0,%1,%2,%3}, {%4,%5,%6,%7}, {%8,%9}, {%10,%10,%10,%10};"
        : "=f"(c[0]), "=f"(c[1]), "=f"(c[2]), "=f"(c[3]) : "r"(a0), "r"(a1), "r"(a2), "r"(a3), "r"(b0), "r"(b1), "f"(0.f));
}
__device__ __forceinline__ float uf(uint32_t x) { return __uint_as_float(x); }
__device__ __forceinline__ void cs2048(int j, float& c, float& s) {
    j = ((j & 2047) ^ 1024) - 1024;
    float a = (float)j * 3.0679615757712823e-3f;
    c = __cosf(a); s = __sinf(a);
}
__device__ __forceinline__ void row_stats(const uint32_t (&w)[8], int g, float& mu, float& var) {
    float st[4], s2[4];
    const uint32_t ONES = 0x3F803F80u;
    mma0(st, w[0], ONES, w[1], ONES, w[0], w[1]);
    mma0(s2, w[2], ONES, w[3], ONES, w[2], w[3]);
    mma(st, w[4], ONES, w[5], ONES, w[4], w[5]);
    mma(s2, w[6], ONES, w[7], ONES, w[6], w[7]);
    float sq = (g & 1) ? st[1] + s2[1] : st[0] + s2[0];
    sq = __shfl_sync(~0u, sq, 4 * g + (g >> 1));
    float sm = (st[2] + st[3]) + (s2[2] + s2[3]);
    sm += __shfl_xor_sync(~0u, sm, 1); sq += __shfl_xor_sync(~0u, sq, 4);
    sm += __shfl_xor_sync(~0u, sm, 2); sq += __shfl_xor_sync(~0u, sq, 8);
    sq += __shfl_xor_sync(~0u, sq, 16);
    mu = sm * (1.f / 448.f);
    var = fmaxf(fmaf(sq, 1.f / 448.f, -mu * mu), 0.f);
}
__device__ __forceinline__ uint4 ld_relaxed4(const void* p) { uint4 x; asm volatile("ld.relaxed.gpu.global.v4.u32 {%0,%1,%2,%3}, [%4];" : "=r"(x.x), "=r"(x.y), "=r"(x.z), "=r"(x.w) : "l"(p) : "memory"); return x; }
__device__ __forceinline__ bool stale(const uint4 (&q)[4], uint32_t tag) {
    uint32_t a, b, c;
    asm("lop3.b32 %0, %1, %2, %3, 0x7E;" : "=r"(a) : "r"(q[0].x), "r"(q[1].x), "r"(tag));
    asm("lop3.b32 %0, %1, %2, %3, 0x7E;" : "=r"(b) : "r"(q[2].x), "r"(q[3].x), "r"(tag));
    asm("lop3.b32 %0, %1, %2, 1, 0xA8;" : "=r"(c) : "r"(a), "r"(b));
    return __any_sync(~0u, c != 0);
}
__device__ __forceinline__ void refetch(uint4 (&q)[4], const uint4* src, int step, uint32_t tag) {
#pragma unroll 1
    for (int it = 0; it < SPIN_LIMIT; it++) {
        spin_until(clk32(), 150);
#pragma unroll
        for (int j = 0; j < 4; j++) if ((q[j].x ^ tag) & 1) q[j] = ld_relaxed4(src + (size_t)j * step);
        if (!stale(q, tag)) break;
    }
}
template <uint32_t BHI> __device__ __forceinline__ void wgmma4_n112(float (&d)[56], uint32_t alo, uint32_t blo_) {
    asm volatile("{\n.reg .b64 da, db;\n.reg .b32 a, b;\nadd.u32 a, %56, 0;\nadd.u32 b, %57, 0;\nmov.b64 da, {a, %58};\nmov.b64 db, {b, %59};\nwgmma.mma_async.sync.aligned.m64n112k16.f32.bf16.bf16 {%0, %1, %2, %3, %4, %5, %6, %7, %8, %9, %10, %11, %12, %13, %14, %15, %16, %17, %18, %19, %20, %21, %22, %23, %24, %25, %26, %27, %28, %29, %30, %31, %32, %33, %34, %35, %36, %37, %38, %39, %40, %41, %42, %43, %44, %45, %46, %47, %48, %49, %50, %51, %52, %53, %54, %55}, da, db, 1, 1, 1, 1, 1;\nadd.u32 a, %56, 128;\nadd.u32 b, %57, 224;\nmov.b64 da, {a, %58};\nmov.b64 db, {b, %59};\nwgmma.mma_async.sync.aligned.m64n112k16.f32.bf16.bf16 {%0, %1, %2, %3, %4, %5, %6, %7, %8, %9, %10, %11, %12, %13, %14, %15, %16, %17, %18, %19, %20, %21, %22, %23, %24, %25, %26, %27, %28, %29, %30, %31, %32, %33, %34, %35, %36, %37, %38, %39, %40, %41, %42, %43, %44, %45, %46, %47, %48, %49, %50, %51, %52, %53, %54, %55}, da, db, 1, 1, 1, 1, 1;\nadd.u32 a, %56, 256;\nadd.u32 b, %57, 448;\nmov.b64 da, {a, %58};\nmov.b64 db, {b, %59};\nwgmma.mma_async.sync.aligned.m64n112k16.f32.bf16.bf16 {%0, %1, %2, %3, %4, %5, %6, %7, %8, %9, %10, %11, %12, %13, %14, %15, %16, %17, %18, %19, %20, %21, %22, %23, %24, %25, %26, %27, %28, %29, %30, %31, %32, %33, %34, %35, %36, %37, %38, %39, %40, %41, %42, %43, %44, %45, %46, %47, %48, %49, %50, %51, %52, %53, %54, %55}, da, db, 1, 1, 1, 1, 1;\nadd.u32 a, %56, 384;\nadd.u32 b, %57, 672;\nmov.b64 da, {a, %58};\nmov.b64 db, {b, %59};\nwgmma.mma_async.sync.aligned.m64n112k16.f32.bf16.bf16 {%0, %1, %2, %3, %4, %5, %6, %7, %8, %9, %10, %11, %12, %13, %14, %15, %16, %17, %18, %19, %20, %21, %22, %23, %24, %25, %26, %27, %28, %29, %30, %31, %32, %33, %34, %35, %36, %37, %38, %39, %40, %41, %42, %43, %44, %45, %46, %47, %48, %49, %50, %51, %52, %53, %54, %55}, da, db, 1, 1, 1, 1, 1;\n}\n"
        : "+f"(d[0]), "+f"(d[1]), "+f"(d[2]), "+f"(d[3]), "+f"(d[4]), "+f"(d[5]), "+f"(d[6]), "+f"(d[7]), "+f"(d[8]), "+f"(d[9]), "+f"(d[10]), "+f"(d[11]), "+f"(d[12]), "+f"(d[13]), "+f"(d[14]), "+f"(d[15]), "+f"(d[16]), "+f"(d[17]), "+f"(d[18]), "+f"(d[19]), "+f"(d[20]), "+f"(d[21]), "+f"(d[22]), "+f"(d[23]), "+f"(d[24]), "+f"(d[25]), "+f"(d[26]), "+f"(d[27]), "+f"(d[28]), "+f"(d[29]), "+f"(d[30]), "+f"(d[31]), "+f"(d[32]), "+f"(d[33]), "+f"(d[34]), "+f"(d[35]), "+f"(d[36]), "+f"(d[37]), "+f"(d[38]), "+f"(d[39]), "+f"(d[40]), "+f"(d[41]), "+f"(d[42]), "+f"(d[43]), "+f"(d[44]), "+f"(d[45]), "+f"(d[46]), "+f"(d[47]), "+f"(d[48]), "+f"(d[49]), "+f"(d[50]), "+f"(d[51]), "+f"(d[52]), "+f"(d[53]), "+f"(d[54]), "+f"(d[55])
        : "r"(alo), "r"(blo_), "n"(0x40000040), "n"(BHI));
}

__device__ __forceinline__ float gelu(float x) {
    float y = x * fmaf(x * x, 0.035677408136300125f, 0.7978845608028654f);
    float t; asm("tanh.approx.f32 %0, %1;" : "=f"(t) : "f"(y));
    float hx = 0.5f * x;
    return fmaf(hx, t, hx);
}
__device__ __forceinline__ void wait_count(const unsigned* p, unsigned tgt) {
#pragma unroll 1
    for (int it = 0; it < SPIN_LIMIT; it++) if (__all_sync(~0u, (int)(ld_relaxed(p) - tgt) >= 0)) break;
}
__device__ __forceinline__ void poll_flags(const unsigned* p, unsigned tgt, uint32_t go, bool active) {
    bool pend = active;
#pragma unroll 1
    for (int it = 0; it < SPIN_LIMIT; it++) {
        bool ok = (int)(ld_acquire(p) - tgt) >= 0;
        if (pend && ok) { mbar_arrive(go); pend = false; }
        if (!__any_sync(~0u, pend)) break;
    }
    if (pend) mbar_arrive(go);
}

__device__ __forceinline__ void fft128(uint32_t (&wd)[4][4], const uint32_t (&tb)[48], const float (&wr)[4][4], const float (&wi)[4][4]) {
#pragma unroll
    for (int cp = 0; cp < 2; cp++) {
        uint32_t ar[4], ai[4];
#pragma unroll
        for (int h = 0; h < 2; h++) {
            const int c = 2 * cp + h;
            float re[4], im[4];
            mma0(re, tb[0], tb[1], tb[2], tb[3], wd[0][c], wd[1][c]);
            mma0(im, tb[8], tb[9], tb[10], tb[11], wd[0][c], wd[1][c]);
            mma(re, tb[4], tb[5], tb[6], tb[7], wd[2][c], wd[3][c]);
            mma(im, tb[12], tb[13], tb[14], tb[15], wd[2][c], wd[3][c]);
            float r2[4], i2[4];
#pragma unroll
            for (int i = 0; i < 4; i++) {
                float cr = uf(tb[16 + 2 * i]), ci = uf(tb[17 + 2 * i]);
                r2[i] = re[i] * cr - im[i] * ci; i2[i] = re[i] * ci + im[i] * cr;
            }
            const uint32_t a0 = pk(r2[0], r2[1]), a1 = pk(r2[2], r2[3]), a2 = pk(i2[0], i2[1]), a3 = pk(i2[2], i2[3]);
            mma0(re, a0, a1, a2, a3, tb[40], tb[41]);
            mma0(im, a0, a1, a2, a3, tb[42], tb[43]);
#pragma unroll
            for (int i = 0; i < 4; i++) {
                r2[i] = re[i] * wr[c][i] - im[i] * wi[c][i]; i2[i] = re[i] * wi[c][i] + im[i] * wr[c][i];
            }
            float d0[4], d1[4];
            mma0(d0, tb[40], tb[41], tb[42], tb[43], pk(r2[0], r2[1]), pk(i2[0], i2[1]));
            mma0(d1, tb[40], tb[41], tb[42], tb[43], pk(r2[2], r2[3]), pk(i2[2], i2[3]));
#pragma unroll
            for (int e = 0; e < 2; e++) {
                float cr = uf(tb[24 + 2 * e]), ci = uf(tb[25 + 2 * e]);
                r2[e] = d0[e] * cr - d0[2 + e] * ci; i2[e] = d0[e] * ci + d0[2 + e] * cr;
                cr = uf(tb[28 + 2 * e]); ci = uf(tb[29 + 2 * e]);
                r2[2 + e] = d1[e] * cr - d1[2 + e] * ci; i2[2 + e] = d1[e] * ci + d1[2 + e] * cr;
            }
            ar[h] = pk(r2[0], r2[1]); ar[2 + h] = pk(r2[2], r2[3]); ai[h] = pk(i2[0], i2[1]); ai[2 + h] = pk(i2[2], i2[3]);
        }
#pragma unroll
        for (int tau = 0; tau < 2; tau++) {
            float re[4], im[4];
            mma0(re, ar[0], ar[1], ar[2], ar[3], tb[32 + 4 * tau], tb[33 + 4 * tau]);
            mma0(im, ai[0], ai[1], ai[2], ai[3], tb[32 + 4 * tau], tb[33 + 4 * tau]);
            mma(re, ai[0], ai[1], ai[2], ai[3], tb[44 + 2 * tau], tb[45 + 2 * tau]);
            mma(im, ar[0], ar[1], ar[2], ar[3], tb[34 + 4 * tau], tb[35 + 4 * tau]);
#pragma unroll
            for (int e = 0; e < 2; e++) { wd[2 * tau + e][2 * cp] = pk(re[e], im[e]); wd[2 * tau + e][2 * cp + 1] = pk(re[2 + e], im[2 + e]); }
        }
    }
}

__device__ __forceinline__ void fence_acc(float (&acc)[56]) {
#pragma unroll
    for (int i = 0; i < 56; i++) asm volatile("" : "+f"(acc[i]) :: "memory");
}
template <int which>
__device__ __forceinline__ void gemm_loop(float (&acc)[56], uint32_t sb) {
    constexpr int n0 = which ? 32 : 0, nkb = which ? 28 : 32;
    constexpr uint32_t BHI = which == 0 ? (0xC0000000u | 112u) : 8u;
    const uint32_t ln = threadIdx.x & 31;
    const uint32_t abase = (sb & 0x3FFFF) >> 4, bbase = (((sb + OFF_A) & 0x3FFFF) >> 4) | ((which == 0 ? 16u : 112u) << 16);
    uint32_t alo = abase + (n0 % NW) * (WST >> 4), blo_ = bbase + (n0 % NA) * (AST >> 4);
    uint32_t bar = sb + OFF_BAR + n0 * 8;
    const uint32_t bar_end = bar + nkb * 8;
    fence_acc(acc);
    __syncwarp();
    mbar_wait0(bar);
    asm volatile("wgmma.fence.sync.aligned;" ::: "memory");
    wgmma4_n112<BHI>(acc, alo, blo_);
    asm volatile("wgmma.commit_group.sync.aligned;" ::: "memory");
    bar += 8;
#pragma unroll 1
    while (bar != bar_end) {
        alo += WST >> 4; if (alo == abase + NW * (WST >> 4)) alo = abase;
        blo_ += AST >> 4; if (blo_ == bbase + NA * (AST >> 4)) blo_ = bbase;
        mbar_wait0(bar);
        asm volatile("wgmma.fence.sync.aligned;" ::: "memory");
        wgmma4_n112<BHI>(acc, alo, blo_);
        asm volatile("wgmma.commit_group.sync.aligned;" ::: "memory");
        asm volatile("wgmma.wait_group.sync.aligned 1;" ::: "memory");
        if (ln < 2) arrive_remote(bar + (480 - 8), ln);
        bar += 8;
    }
    asm volatile("wgmma.wait_group.sync.aligned 0;" ::: "memory");
    fence_acc(acc);
    if (ln < 2) arrive_remote(bar + (480 - 8), ln);
}

constexpr int WB2 = 6, PF_AHEAD = 12, WC_DELAY = 1200;

__global__ void __launch_bounds__(NTHR, 1)
fused_kernel(const __nv_bfloat16* __restrict__ x, const uint4* __restrict__ tab, Scratch* __restrict__ scr,
             const __nv_bfloat16* __restrict__ b1, const __nv_bfloat16* __restrict__ b2, __nv_bfloat16* __restrict__ out,
             const __grid_constant__ CUtensorMap tm_w1, const __grid_constant__ CUtensorMap tm_w2,
             const __grid_constant__ CUtensorMap tm_wr, const __grid_constant__ CUtensorMap tm_wi,
             const __grid_constant__ CUtensorMap tm_h) {
    extern __shared__ __align__(1024) unsigned char sm[];
    const uint32_t sb = s2u(sm);
    const int tid = threadIdx.x, lane = tid & 31, g = lane >> 2, t = lane & 3;
    const int bid = blockIdx.x;
    uint2 xv[2][4];
    if (tid < 256) {
        const int r0 = ((tid >> 5) & 3) + 8 * ((tid >> 7) & 1);
        const uint2* xr = (const uint2*)(x + (size_t)(bid + 128 * r0) * 448) + (g >> 1) + 4 * (g & 1) + 16 * t;
#pragma unroll
        for (int r = 0; r < 2; r++) {
            xv[r][0] = __ldg(xr + r * 57344); xv[r][1] = __ldg(xr + r * 57344 + 8);
            if (t < 3) { xv[r][2] = __ldg(xr + r * 57344 + 64); xv[r][3] = __ldg(xr + r * 57344 + 72); }
            else { xv[r][2] = make_uint2(0, 0); xv[r][3] = make_uint2(0, 0); }
        }
    }
    const int warp = __shfl_sync(~0u, tid >> 5, 0);
    const uint32_t full = sb + OFF_BAR, done = full + 480, go = done + 480;
    const uint32_t wt_full = go + 192, fft_done = wt_full + 16, c_go = fft_done + 8;
    const uint32_t init_done = c_go + 8, h_full = init_done + 8, h_go = h_full + 8, bt_full = h_go + 8, hs_free = bt_full + 8, x_free = hs_free + 8;
    volatile unsigned* s_epoch = (volatile unsigned*)(sm + OFF_MISC);
    const bool full_b = bid < 112;
    const int tile = ((bid >> 1) & 7) | ((bid >> 5) << 3), dt = ((bid >> 3) & 2) | (bid & 1);
    const bool has_g1 = tile < 28;
    const int pb_k1 = full_b ? bid / 7 : bid - 112;
    const int pb_tile = pb_k1 * 8 + (full_b ? bid - pb_k1 * 7 : 7);
    const int w_e = 225 * pb_k1 + 32 * (pb_tile & 7);

    if (warp >= 8) {
        if (warp == 11) {
            if (lane == 0) {
#pragma unroll
                for (int i = 0; i < 10; i++) mbar_init(wt_full + i * 8, i >= 8 ? 4 : 1);
                asm volatile("fence.mbarrier_init.release.cluster;" ::: "memory");
                mbar_expect(wt_full, 20480 + 12800);
                if (full_b) mbar_expect(bt_full, 16384);
                mbar_expect(h_full, AST);
            }
            __syncwarp();
            asm volatile("bar.arrive 2, 384;" ::: "memory");
            tma2d_e(sb + OFF_WR, &tm_wr, w_e & ~7, 0, wt_full);
            tma2d_e(sb + OFF_WI, &tm_wi, w_e & ~7, 0, wt_full);
            bulk_load_e(sb + OFF_TAB, tab, 12800, wt_full);
            if (lane == 0) {
#pragma unroll
                for (int i = 0; i < 32; i++) mbar_init(full + i * 8, 1);
#pragma unroll
                for (int i = 0; i < 32; i++) mbar_expect(full + i * 8, WST + AST);
                asm volatile("fence.mbarrier_init.release.cluster;" ::: "memory");
                mbar_arrive(init_done);
            }
            __syncwarp();
            asm volatile("barrier.cluster.arrive.relaxed.aligned;\nbarrier.cluster.wait.aligned;" ::: "memory");
            const int crank = bid & 1;
            const int nb = has_g1 ? 0 : 32;
            auto ring = [&](int n) {
                if (n < 32) tma3d_mc_e(sb + (n % NW) * WST, &tm_w1, tile * 64, 0, n * 4, full + n * 8);
                else tma2d_mc_e(sb + (n % NW) * WST, &tm_w2, tile * 64, (n - 32) * 64, full + n * 8);
            };
            auto pref = [&](int n) {
                if (n < 32) pf3d_e(&tm_w1, tile * 64, 0, n * 4);
                else if (n < 60) pf2d_e(&tm_w2, tile * 64, (n - 32) * 64);
            };
            int rn = nb + crank, pn = nb + NW + ((dt - NW) & 3);
            auto batch = [&](int upto) {
#pragma unroll 1
                for (; rn < nb + min(upto, NW); rn += 2) ring(rn);
#pragma unroll 1
                for (; pn < nb + upto; pn += 4) pref(pn);
            };
            mbar_wait0(bt_full); if (!full_b) spin_until(clk32(), 1000);
            batch(WB2);
            mbar_wait0(c_go); spin_until(clk32(), WC_DELAY);
            batch(NW);
            __syncwarp();
            if (!has_g1) { mbar_wait0(fft_done); spin_until(clk32(), 4000); batch(28); }
#pragma unroll 1
            for (int n = nb + NW + ((crank ^ nb ^ NW) & 1); n < 60; n += 2) {
                mbar_wait0(done + (n - NW) * 8);
                ring(n);
                if (pn < n + PF_AHEAD) { pref(pn); pn += 4; }
            }
            return;
        }
        if (warp == 8) {
#pragma unroll
            for (int m = 0; m < 2; m++) {
                float c[4], sn[4];
                const uint32_t dst = sb + OFF_CS + m * 1024 + lane * 16;
#pragma unroll
                for (int i = 0; i < 4; i++) { cs2048((t + 4 * i) * (bid + 128 * (8 * m + g)), c[i], sn[i]); c[i] *= 1.f / (2048.f * 448.f); sn[i] *= 1.f / (2048.f * 448.f); }
                sts4(dst, pk(c[0], -sn[0]), pk(sn[0], c[0]), pk(c[1], -sn[1]), pk(sn[1], c[1]));
                sts4(dst + 512, pk(c[2], -sn[2]), pk(sn[2], c[2]), pk(c[3], -sn[3]), pk(sn[3], c[3]));
            }
            asm volatile("barrier.cluster.arrive.relaxed.aligned;" ::: "memory");
            asm volatile("bar.arrive 2, 384;" ::: "memory");
            return;
        }
        if (warp == 9) {
            if (lane == 0) {
#pragma unroll
                for (int i = 32; i < 60; i++) mbar_init(full + i * 8, 1);
#pragma unroll
                for (int i = 32; i < 60; i++) mbar_expect(full + i * 8, WST + AST);
                asm volatile("fence.mbarrier_init.release.cluster;" ::: "memory");
            }
        } else if (lane == 0) {
            const unsigned e = ld_relaxed(&scr->sync[0]) + 1;
#pragma unroll
            for (int i = 0; i < 60; i++) mbar_init(done + i * 8, 8);
#pragma unroll
            for (int i = 0; i <= NA + 1; i++) { mbar_init(go + i * 8, i < NA ? 1 : i == NA ? 16 - NA : 16); mbar_init(go + (12 + i) * 8, i < NA ? 1 : i == NA ? 16 - NA : 12); }
            asm volatile("fence.mbarrier_init.release.cluster;" ::: "memory");
            *s_epoch = e;
        }
        __syncwarp();
        asm volatile("barrier.cluster.arrive.relaxed.aligned;" ::: "memory");
        asm volatile("bar.sync 2, 384;" ::: "memory");
        const unsigned ep1 = *s_epoch;
        if (warp == 9) {
            mbar_wait0(init_done);
            asm volatile("bar.sync 3, 288;" ::: "memory");
            if (lane == 0) { mbar_arrive(fft_done); red_release(&scr->sync[96 + (bid >> 2)]); }
            __syncwarp();
            if (has_g1) {
                poll_flags(&scr->sync[96 + lane], ep1 * 4, go + (min(lane, NA) + (lane >> 4)) * 8, true);
                mbar_wait0(done + 31 * 8);
            } else __nanosleep(4000);
            poll_flags(&scr->sync[128 + dt * 32 + lane], ep1, go + (12 + min(lane, NA) + (lane >> 4)) * 8, lane < 28);
            mbar_wait0(done + 40 * 8);
            asm volatile("prefetch.tensormap [%0];" :: "l"(&tm_h) : "memory");
            poll_flags(&scr->sync[256], ep1 * NCTA, h_go, lane == 0);
            return;
        }
        spin_until(clk32(), 150);
        if (lane == 0) red_relaxed(&scr->sync[32]);
        asm volatile("bar.sync 6, 288;" ::: "memory");
        fence_async_s();
        wait_count(&scr->sync[32], ep1 * NCTA);
        __syncwarp();
        if (full_b) bulk_load_e(sb + OFF_BT, scr->S1 + pb_tile * 1024, 16384, bt_full);
        else if (lane == 0) mbar_arrive(bt_full);
        mbar_wait0(bt_full);
        wait_count(&scr->sync[64], ep1 * NCTA);
        if (lane == 0) { mbar_arrive(c_go); if (bid == 0) scr->sync[0] = ep1; }
        __syncwarp();
        mbar_wait0(fft_done);
        mbar_wait0(init_done);
        fence_async_s();
        if (has_g1) {
            const uint4* src = scr->hp + dt * 896;
            uint32_t dst = sb + OFF_A;
#pragma unroll 1
            for (int k = 0; k < NA; k++) {
                if (k == NA - 1) mbar_wait0(hs_free);
                mbar_wait0(go + k * 8);
                fence_async_g();
                bulk_load_e(dst, src, AST, full + k * 8);
                __syncwarp();
                src += 3584; dst += AST;
            }
            dst = sb + OFF_A;
#pragma unroll 1
            for (int hf = 0; hf < 2; hf++) {
                mbar_wait0(go + (NA + hf) * 8);
                fence_async_g();
#pragma unroll 1
                for (int k = hf ? 16 : NA; k < 16 + 16 * hf; k++) {
                    mbar_wait0(done + (k - NA) * 8);
                    bulk_load_e(dst, src, AST, full + k * 8);
                    src += 3584; dst += AST; if (dst == sb + OFF_A + NA * AST) dst = sb + OFF_A;
                }
            }
            mbar_wait0(done + 31 * 8);
        } else mbar_wait0(hs_free);
        {
            const uint4* src = scr->u + dt * 896;
            uint32_t dst = sb + OFF_A + (32 % NA) * AST;
#pragma unroll 1
            for (int k = 32; k < 32 + NA; k++) {
                if (k == 30 + NA && has_g1) mbar_wait0(x_free);
                mbar_wait0(go + (k - 20) * 8);
                fence_async_g();
                bulk_load_e(dst, src, AST, full + k * 8);
                __syncwarp();
                src += 3584; dst += AST; if (dst == sb + OFF_A + NA * AST) dst = sb + OFF_A;
            }
#pragma unroll 1
            for (int hf = 0; hf < 2; hf++) {
                mbar_wait0(go + (12 + NA + hf) * 8);
                fence_async_g();
#pragma unroll 1
                for (int k = hf ? 48 : 32 + NA; k < 48 + 12 * hf; k++) {
                    mbar_wait0(done + (k - NA) * 8);
                    bulk_load_e(dst, src, AST, full + k * 8);
                    src += 3584; dst += AST; if (dst == sb + OFF_A + NA * AST) dst = sb + OFF_A;
                }
            }
        }
        mbar_wait0(done + (60 - NA) * 8);
        mbar_wait0(h_go);
        fence_async_g();
        tma2d_e(sb + OFF_A + (60 % NA) * AST, &tm_h, dt * 112, tile * 64, h_full);
        return;
    }

    const int rho = 32 * (bid >> 5) + 4 * (bid & 7) + ((bid >> 3) & 3);
    const int row0 = (warp & 3) + 8 * (warp >> 2);
    uint32_t tag, cw[2];
    {
        {
            const uint32_t dst = sb + OFF_BT + lane * 16;
            float c[4], sn[4];
            if (warp < 4) {
                cs448(g * (4 * t + warp), c[0], sn[0]); cs448(g * (4 * t + warp + 16), c[1], sn[1]);
                sts4(dst + (1 + warp) * 512, __float_as_uint(c[0]), __float_as_uint(-sn[0]), __float_as_uint(c[1]), __float_as_uint(-sn[1]));
                const int k1 = 8 * (warp >> 1) + g, s0 = bid + 128 * (t + 8 * (warp & 1));
                cs2048(k1 * s0, c[2], sn[2]); cs2048(k1 * (s0 + 512), c[3], sn[3]);
                sts4(dst + (12 + warp) * 512, pk(c[2], sn[2]), pk(-sn[2], c[2]), pk(c[3], sn[3]), pk(-sn[3], c[3]));
            } else if (warp < 6) {
#pragma unroll
                for (int i = 0; i < 4; i++) cs448(14 * (((4 * t + i) * (2 * g + warp - 4)) & 31), c[i], sn[i]);
                const uint32_t c0 = pk(c[0], c[1]), c1 = pk(c[2], c[3]), s0 = pk(sn[0], sn[1]), s1 = pk(sn[2], sn[3]);
                const uint32_t H = 0x80000000u, d3 = dst + (5 + 3 * (warp - 4)) * 512;
                sts4(d3, c0, c1, s0, s1);
                sts4(d3 + 512, neg2(s0), neg2(s1), c0 ^ H, c1 ^ H);
                sts4(d3 + 1024, s0 ^ H, s1 ^ H, c0 ^ 0x8000u, c1 ^ 0x8000u);
            } else if (warp == 6) {
#pragma unroll
                for (int i = 0; i < 4; i++) cs448(32 * ((g * (2 * t + (i & 1) + 8 * (i >> 1))) % 14), c[i], sn[i]);
                const uint32_t z = t < 3 ? ~0u : 0u;
                sts4(dst, pk(c[0], c[1]), pk(-sn[0], -sn[1]), pk(c[2], c[3]) & z, pk(-sn[2], -sn[3]) & z);
            } else sts4(dst + 11 * 512, 0u, 0u, 0u, 0u);
        }
        csync();
        uint32_t ta[44], a3[16];
        ldtab_s(ta, sb + OFF_BT + lane * 16);
        ldtab_s(a3, sb + OFF_BT + 12 * 512 + lane * 16);
        asm volatile("barrier.cluster.arrive.relaxed.aligned;" ::: "memory");
        const uint32_t trow = sb + OFF_T + 4 * warp * TPA;
        const uint32_t tf = keep(trow + 8 * (g + 56 * t));
        const uint32_t tm = keep((g >= 1 && g <= 6) ? trow + 8 * (224 - g - 56 * t) : sb + OFF_T + 15360);
        const uint32_t tm0 = lane == 0 ? trow + 8 * 224 : tm;
        const uint32_t tq = keep(sb + OFF_T + 4 * (t * TPA + 64 * warp + 8 * ((g & 4) | ((g & 1) << 1) | ((g >> 1) & 1))));
        const int dch = (4 * (t >> 1) + (t & 1)) ^ (rho & 7);
        const uint4* d0 = keep(scr->S1 + (g * 8 + warp) * 1024 + rho * 8 + dch);
        const uint4* d1 = keep(scr->S1 + (g * 8 + warp) * 1024 + rho * 8 + (dch ^ 2));
        uint32_t zero;
        asm volatile("ld.volatile.shared.u32 %0, [%1];" : "=r"(zero) : "r"(sb + OFF_BT + 11 * 512 + ((tf ^ tm ^ tq ^ (uint32_t)(uint64_t)d0 ^ (uint32_t)(uint64_t)d1 ^ (uint32_t)((uint64_t)d0 >> 32)) & 0x1fc)) : "memory");
        uint32_t ar[2][4], ai[2][4];
        float inv[2];
#pragma unroll
        for (int r = 0; r < 2; r++) {
            cw[r] = __shfl_sync(~0u, xv[r][0].x, zero);
            cw[r] = __byte_perm(cw[r], cw[r], 0x1010);
            const uint32_t cw2 = t < 3 ? cw[r] : 0u;
            uint32_t bw[8];
            {
                uint32_t p0 = hsub2(xv[r][0].x, cw[r]), p1 = hsub2(xv[r][1].x, cw[r]), p2 = hsub2(xv[r][2].x, cw2), p3 = hsub2(xv[r][3].x, cw2);
                bw[0] = __byte_perm(p0, p1, 0x5410); bw[1] = __byte_perm(p2, p3, 0x5410);
                bw[2] = __byte_perm(p0, p1, 0x7632); bw[3] = __byte_perm(p2, p3, 0x7632);
                p0 = hsub2(xv[r][0].y, cw[r]); p1 = hsub2(xv[r][1].y, cw[r]); p2 = hsub2(xv[r][2].y, cw2); p3 = hsub2(xv[r][3].y, cw2);
                bw[4] = __byte_perm(p0, p1, 0x5410); bw[5] = __byte_perm(p2, p3, 0x5410);
                bw[6] = __byte_perm(p0, p1, 0x7632); bw[7] = __byte_perm(p2, p3, 0x7632);
            }
            float ur[4], ui[4], vr[4], vi[4];
#pragma unroll
            for (int j = 0; j < 4; j++) {
                float c[4];
                mma0(c, ta[0], ta[1], ta[2], ta[3], bw[2 * j], bw[2 * j + 1]);
                float cr = uf(ta[4 + 4 * j]), ci = uf(ta[5 + 4 * j]);
                float r0 = c[0] * cr - c[2] * ci, i0 = c[0] * ci + c[2] * cr;
                cr = uf(ta[6 + 4 * j]); ci = uf(ta[7 + 4 * j]);
                ur[j] = fmaf(c[1], cr, fmaf(-c[3], ci, r0)); ui[j] = fmaf(c[1], ci, fmaf(c[3], cr, i0));
                vr[j] = fmaf(2.f, r0, -ur[j]); vi[j] = fmaf(2.f, i0, -ui[j]);
            }
            float mu, var;
            row_stats(bw, g, mu, var);
            inv[r] = rsq(var + 1e-5f);
            ar[0][r] = pk(ur[0], ur[1]); ar[0][2 + r] = pk(ur[2], ur[3]); ai[0][r] = pk(ui[0], ui[1]); ai[0][2 + r] = pk(ui[2], ui[3]);
            ar[1][r] = pk(vr[0], vr[1]); ar[1][2 + r] = pk(vr[2], vr[3]); ai[1][r] = pk(vi[0], vi[1]); ai[1][2 + r] = pk(vi[2], vi[3]);
        }
#pragma unroll
        for (int par = 0; par < 2; par++) {
            const int o = 20 + 12 * par;
#pragma unroll
            for (int qt = 0; qt < 2; qt++) {
                const int oc = o + 6 * qt, os = oc + 2, on = oc + 4;
                float re[4], im[4];
                mma0(re, ar[par][0], ar[par][1], ar[par][2], ar[par][3], ta[oc], ta[oc + 1]);
                mma0(im, ai[par][0], ai[par][1], ai[par][2], ai[par][3], ta[qt ? on : oc], ta[(qt ? on : oc) + 1]);
                mma(re, ai[par][0], ai[par][1], ai[par][2], ai[par][3], ta[os], ta[os + 1]);
                mma(im, ar[par][0], ar[par][1], ar[par][2], ar[par][3], ta[qt ? os : on], ta[(qt ? os : on) + 1]);
#pragma unroll
                for (int e = 0; e < 2; e++) {
                    const int i = 2 * e + par;
                    sts2(qt ? (i == 0 ? tm0 : tm) - 112 * i : tf + 112 * i, pk(re[e] * inv[0], im[e] * inv[0]), pk(re[2 + e] * inv[1], im[2 + e] * inv[1]));
                }
            }
        }
        if (lane == 0) sts2(trow, 0u, 0u);
        asm volatile("bar.sync 2, 384;" ::: "memory");
        const uint4 q0 = lds4(tq), q1 = lds4(tq + 16), q2 = lds4(tq + 16 * TPA), q3 = lds4(tq + 16 * TPA + 16);
        tag = *s_epoch & 1;
        float c[2][4][4];
#pragma unroll
        for (int m = 0; m < 2; m++) {
            mma0(c[m][0], a3[8 * m], a3[8 * m + 1], a3[8 * m + 2], a3[8 * m + 3], q0.x, q0.y);
            mma0(c[m][1], a3[8 * m], a3[8 * m + 1], a3[8 * m + 2], a3[8 * m + 3], q0.z, q0.w);
            mma0(c[m][2], a3[8 * m], a3[8 * m + 1], a3[8 * m + 2], a3[8 * m + 3], q1.x, q1.y);
            mma0(c[m][3], a3[8 * m], a3[8 * m + 1], a3[8 * m + 2], a3[8 * m + 3], q1.z, q1.w);
            mma(c[m][0], a3[8 * m + 4], a3[8 * m + 5], a3[8 * m + 6], a3[8 * m + 7], q2.x, q2.y);
            mma(c[m][1], a3[8 * m + 4], a3[8 * m + 5], a3[8 * m + 6], a3[8 * m + 7], q2.z, q2.w);
            mma(c[m][2], a3[8 * m + 4], a3[8 * m + 5], a3[8 * m + 6], a3[8 * m + 7], q3.x, q3.y);
            mma(c[m][3], a3[8 * m + 4], a3[8 * m + 5], a3[8 * m + 6], a3[8 * m + 7], q3.z, q3.w);
        }
        const bool p0 = warp < 7 || t < 2, p1 = warp < 7;
        stg4p<0>(d0, p0, tagw(pk(c[0][0][0], c[0][0][2]), tag), pk(c[0][1][0], c[0][1][2]), pk(c[0][2][0], c[0][2][2]), pk(c[0][3][0], c[0][3][2]));
        stg4p<0>(d1, p1, tagw(pk(c[0][0][1], c[0][0][3]), tag), pk(c[0][1][1], c[0][1][3]), pk(c[0][2][1], c[0][2][3]), pk(c[0][3][1], c[0][3][3]));
        stg4p<1048576>(d0, p0, tagw(pk(c[1][0][0], c[1][0][2]), tag), pk(c[1][1][0], c[1][1][2]), pk(c[1][2][0], c[1][2][2]), pk(c[1][3][0], c[1][3][2]));
        stg4p<1048576>(d1, p1, tagw(pk(c[1][0][1], c[1][0][3]), tag), pk(c[1][1][1], c[1][1][3]), pk(c[1][2][1], c[1][2][3]), pk(c[1][3][1], c[1][3][3]));
        asm volatile("bar.arrive 6, 288;" ::: "memory");
#pragma unroll
        for (int r = 0; r < 2; r++) {
            const uint32_t xs = sb + OFF_XS + (2 * warp + r) * 1120 + 8 * (g >> 1) + 32 * (g & 1) + 160 * t;
            asm volatile("st.shared.v2.u32 [%0], {%1,%2};" :: "r"(xs), "r"(xv[r][0].x), "r"(xv[r][0].y) : "memory");
            asm volatile("st.shared.v2.u32 [%0], {%1,%2};" :: "r"(xs + 80), "r"(xv[r][1].x), "r"(xv[r][1].y) : "memory");
            if (t < 3) {
                asm volatile("st.shared.v2.u32 [%0], {%1,%2};" :: "r"(xs + 640), "r"(xv[r][2].x), "r"(xv[r][2].y) : "memory");
                asm volatile("st.shared.v2.u32 [%0], {%1,%2};" :: "r"(xs + 720), "r"(xv[r][3].x), "r"(xv[r][3].y) : "memory");
            }
        }
        __syncwarp();
    }
    mbar_wait0(wt_full);
    if (full_b || warp == 0) {
        uint32_t tb[48];
        float wr[4][4], wi[4][4];
        uint32_t wx = 0;
        {
            const unsigned short* WR = (const unsigned short*)(sm + OFF_WR) + (w_e & 7) + 4 * warp;
#pragma unroll
            for (int i = 0; i < 4; i++) {
                const int m = g + 8 * (i >> 1) + 16 * (2 * t + (i & 1));
#pragma unroll
                for (int c = 0; c < 4; c++) {
                    wr[c][i] = uf((uint32_t)WR[m * 40 + c] << 16); wi[c][i] = uf((uint32_t)WR[m * 40 + c + 5120] << 16);
                    asm("lop3.b32 %0, %0, %1, %2, 0xFE;" : "+r"(wx) : "r"(__float_as_uint(wr[c][i])), "r"(__float_as_uint(wi[c][i])));
                }
            }
        }
        ldtab_s(tb, sb + OFF_TAB + lane * 16);
        const int off = lane * 8 + (warp ^ (lane & 7));
        const uint32_t bta = keep(sb + OFF_BT + off * 16 + (wx & 0xffffu));
        mbar_wait0(bt_full);
        uint4 q[4];
#pragma unroll
        for (int j = 0; j < 4; j++) q[j] = lds4(bta + j * 4096);
        if (!full_b) {
#pragma unroll
            for (int j = 0; j < 4; j++) q[j].x = ~tag;
        }
        if (stale(q, tag)) { refetch(q, scr->S1 + pb_tile * 1024 + off, 256, tag); }
        uint32_t wd[4][4];
#pragma unroll
        for (int j = 0; j < 4; j++) { wd[j][0] = q[j].x & ~1u; wd[j][1] = q[j].y; wd[j][2] = q[j].z; wd[j][3] = q[j].w; }
        fft128(wd, tb, wr, wi);
        if (full_b) {
#pragma unroll
            for (int j = 0; j < 4; j++) sts4(bta + j * 4096, tagw(wd[j][0], tag), wd[j][1], wd[j][2], wd[j][3]);
            fence_async_s();
            csync();
            if (warp < 4) {
                bulk_store_e(scr->S2 + pb_tile * 1024 + warp * 256, sb + OFF_BT + warp * 4096, 4096);
                asm volatile("cp.async.bulk.commit_group;" ::: "memory");
            }
        } else {
#pragma unroll
            for (int j = 0; j < 4; j++) {
                const uint4 v = make_uint4(tagw(wd[j][0], tag), wd[j][1], wd[j][2], wd[j][3]);
                scr->S2[pb_tile * 1024 + off + j * 256] = v; scr->S2[pb_tile * 1024 + (off ^ 1) + j * 256] = v;
            }
        }
        __syncwarp();
        if (tid == 0) red_relaxed(&scr->sync[64]);
    }
    {
        uint32_t a3[16], tc[52], hw[2][8];
        ldtab_s(a3, sb + OFF_CS + lane * 16);
        ldtab_s(tc, sb + OFF_TAB + 12 * 512 + lane * 16);
        const uint4* src = keep(scr->S2 + (t * 8 + warp) * 1024 + rho * 8 + ((warp < 7 ? g : 0) ^ (rho & 7)));
        const uint32_t ts = keep(sb + OFF_T + 4 * (g * TPC + 32 * warp + 8 * t));
        const uint32_t tf = keep(sb + OFF_T + 4 * (row0 * TPC + g + 56 * t)), tm = keep(sb + OFF_T + 4 * (row0 * TPC + 224 - g - 56 * t));
        const uint4 *hp0, *hp1;
        {
            const uint4* hp = scr->hp + (bid >> 2) * 3584 + (2 * (bid & 3) + (warp >> 2)) * 112 + (warp & 3) * 2;
            const int at0 = lane >> 1, at1 = at0 + 16;
            hp0 = keep(hp + ((at0 * 37) >> 8) * (896 - 112) + at0 * 16); hp1 = keep(hp + ((at1 * 37) >> 8) * (896 - 112) + at1 * 16);
        }

#pragma unroll
        for (int r = 0; r < 2; r++) {
            const uint32_t xs = sb + OFF_XS + (2 * warp + r) * 1120 + g * 80 + t * 4;
#pragma unroll
            for (int i = 0; i < 4; i++) { hw[r][i] = lds1(xs + 16 * i); hw[r][4 + i] = g < 6 ? lds1(xs + 640 + 16 * i) : 0u; }
        }
        mbar_wait0(c_go);
        {
            uint4 q[4];
#pragma unroll
            for (int jj = 0; jj < 4; jj++) q[jj] = ld_relaxed4(src + jj * 32768);
            if (stale(q, tag)) { refetch(q, src, 32768, tag); }
#pragma unroll
            for (int jj = 0; jj < 4; jj++) q[jj].x &= ~1u;
#pragma unroll
            for (int m = 0; m < 2; m++) {
                float c[4][4];
                mma0(c[0], a3[8 * m], a3[8 * m + 1], a3[8 * m + 2], a3[8 * m + 3], q[0].x, q[1].x);
                mma0(c[1], a3[8 * m], a3[8 * m + 1], a3[8 * m + 2], a3[8 * m + 3], q[0].y, q[1].y);
                mma0(c[2], a3[8 * m], a3[8 * m + 1], a3[8 * m + 2], a3[8 * m + 3], q[0].z, q[1].z);
                mma0(c[3], a3[8 * m], a3[8 * m + 1], a3[8 * m + 2], a3[8 * m + 3], q[0].w, q[1].w);
                mma(c[0], a3[8 * m + 4], a3[8 * m + 5], a3[8 * m + 6], a3[8 * m + 7], q[2].x, q[3].x);
                mma(c[1], a3[8 * m + 4], a3[8 * m + 5], a3[8 * m + 6], a3[8 * m + 7], q[2].y, q[3].y);
                mma(c[2], a3[8 * m + 4], a3[8 * m + 5], a3[8 * m + 6], a3[8 * m + 7], q[2].z, q[3].z);
                mma(c[3], a3[8 * m + 4], a3[8 * m + 5], a3[8 * m + 6], a3[8 * m + 7], q[2].w, q[3].w);
                sts4p(ts + m * 32 * TPC, warp < 7 || t == 0, pk(c[0][0], c[0][2]), pk(c[1][0], c[1][2]), pk(c[2][0], c[2][2]), pk(c[3][0], c[3][2]));
                sts4p(ts + m * 32 * TPC + 16, warp < 7, pk(c[0][1], c[0][3]), pk(c[1][1], c[1][3]), pk(c[2][1], c[2][3]), pk(c[3][1], c[3][3]));
            }
        }
        csync();
#pragma unroll
        for (int r = 0; r < 2; r++) {
            float eo[2][2][4];
#pragma unroll
            for (int par = 0; par < 2; par++) {
                const uint32_t b00 = lds1(tf + r * 16 * TPC + 56 * par), b01 = lds1(tf + r * 16 * TPC + 56 * (2 + par));
                const uint32_t b10 = lds1(tm + r * 16 * TPC - 56 * par), b11 = lds1(tm + r * 16 * TPC - 56 * (2 + par));
#pragma unroll
                for (int i = 0; i < 2; i++) {
                    const int o = 16 * par + 8 * i;
                    mma0(eo[par][i], tc[o], tc[o + 1], tc[o + 2], tc[o + 3], b00, b01);
                    mma(eo[par][i], tc[o + 4], tc[o + 5], tc[o + 6], tc[o + 7], b10, b11);
                }
            }
#pragma unroll
            for (int rr = 0; rr < 4; rr++) {
                const int i = rr & 1;
                float re[2], im[2];
#pragma unroll
                for (int e = 0; e < 2; e++) {
                    float a = (rr >> 1) ? eo[0][i][e] - eo[1][i][e] : eo[0][i][e] + eo[1][i][e];
                    float b = (rr >> 1) ? eo[0][i][2 + e] - eo[1][i][2 + e] : eo[0][i][2 + e] + eo[1][i][2 + e];
                    float cr = uf(tc[32 + 4 * rr + 2 * e]), ci = uf(tc[33 + 4 * rr + 2 * e]);
                    re[e] = a * cr - b * ci; im[e] = a * ci + b * cr;
                }
                float y[4];
                mma0(y, tc[48], tc[49], tc[50], tc[51], pk(re[0], re[1]), pk(im[0], im[1]));
                hw[r][rr] = hadd2(hw[r][rr], pk(y[0], y[1])); hw[r][4 + rr] = hadd2(hw[r][4 + rr], pk(y[2], y[3]));
            }
            const uint32_t cw2 = g < 6 ? cw[r] : 0u;
            uint32_t dw[8];
#pragma unroll
            for (int i = 0; i < 4; i++) { dw[i] = hsub2(hw[r][i], cw[r]); dw[4 + i] = hsub2(hw[r][4 + i], cw2); }
            float mu, var;
            row_stats(dw, g, mu, var);
            const float inv = rsq(fmaf(var, 1.00001f, 1e-10f));
            const float off = -(mu + blo(cw[r])) * inv;
            uint32_t v[8];
#pragma unroll
            for (int i = 0; i < 8; i++) v[i] = pk(fmaf(blo(hw[r][i]), inv, off), fmaf(bhi(hw[r][i]), inv, off));
            const int sw = r * 8 + ((lane ^ r) & 1);
            stg4p<0>(hp0 + sw, true, v[0], v[1], v[2], v[3]);
            stg4p<0>(hp1 + sw, g < 6, v[4], v[5], v[6], v[7]);
        }
        if (warp < 4) asm volatile("cp.async.bulk.wait_group.read 0;" ::: "memory");
        __syncwarp();
        asm volatile("bar.arrive 3, 288;" ::: "memory");
        const uint32_t hs = sb + OFF_HS + (tid & 127) * 16;
        if (warp < 4) {
#pragma unroll
            for (int i = 0; i < 4; i++) sts4(hs + i * 2048, hw[i >> 1][4 * (i & 1)], hw[i >> 1][4 * (i & 1) + 1], hw[i >> 1][4 * (i & 1) + 2], hw[i >> 1][4 * (i & 1) + 3]);
            asm volatile("bar.arrive 9, 256;" ::: "memory");
        } else {
            asm volatile("bar.sync 9, 256;" ::: "memory");
            uint4 ho[4];
#pragma unroll
            for (int i = 0; i < 4; i++) ho[i] = lds4(hs + i * 2048);
            __syncwarp();
            if (lane == 0) mbar_arrive(hs_free);
            mbar_wait0(init_done);
            uint4* hd = scr->h + (bid + 128 * (warp & 3)) * 56 + lane;
#pragma unroll
            for (int i = 0; i < 8; i++) {
                if (has_g1) mbar_wait0(done + (8 + 2 * i) * 8);
                const uint4 v = i < 4 ? ho[i] : make_uint4(hw[(i >> 1) & 1][4 * (i & 1)], hw[(i >> 1) & 1][4 * (i & 1) + 1], hw[(i >> 1) & 1][4 * (i & 1) + 2], hw[(i >> 1) & 1][4 * (i & 1) + 3]);
                if ((i & 1) == 0 || g < 6) hd[(i >> 1) * (4 * 128 * 56) + (i & 1) * 32] = v;
            }
            if (!has_g1) {
                asm volatile("bar.sync 5, 128;" ::: "memory");
                if (tid == 128) red_release(&scr->sync[256]);
            }
        }
    }
    const int wq = warp & 3;
    float acc[56];
    const uint32_t xch = sb + OFF_A + (30 % NA) * AST + (tid & 127) * 16;
    uint32_t* ub = (uint32_t*)(scr->u + (tile * 4 + dt) * 896) + 2 * wq * 448 + lane;
    mbar_wait0(init_done);
    if (warp < 4) {
        if (!has_g1) return;
        const float bias0 = __bfloat162float(b1[tile * 64 + 16 * wq + g]);
        const float bias1 = __bfloat162float(b1[tile * 64 + 16 * wq + g + 8]);
#pragma unroll
        for (int j = 0; j < 14; j++) { acc[4 * j] = bias0; acc[4 * j + 1] = bias0; acc[4 * j + 2] = bias1; acc[4 * j + 3] = bias1; }
        gemm_loop<0>(acc, sb);
        asm volatile("bar.sync 4, 128;" ::: "memory");
#pragma unroll
        for (int j = 0; j < 7; j++) sts4(xch + j * 2048, __float_as_uint(acc[28 + 4 * j]), __float_as_uint(acc[29 + 4 * j]), __float_as_uint(acc[30 + 4 * j]), __float_as_uint(acc[31 + 4 * j]));
        asm volatile("bar.arrive 7, 256;" ::: "memory");
#pragma unroll
        for (int j = 0; j < 7; j++) {
            ub[j * 32] = pk(gelu(acc[4 * j]), gelu(acc[4 * j + 1]));
            ub[448 + j * 32] = pk(gelu(acc[4 * j + 2]), gelu(acc[4 * j + 3]));
        }
        csync();
        if (tid == 0) { red_release(&scr->sync[128 + dt * 32 + tile]); red_relaxed(&scr->sync[256]); }

    } else {
        const int s0 = tile * 64 + 16 * wq + g;
        const float c0 = __bfloat162float(b2[s0]), c1 = __bfloat162float(b2[s0 + 8]);
#pragma unroll
        for (int j = 0; j < 14; j++) { acc[4 * j] = c0; acc[4 * j + 1] = c0; acc[4 * j + 2] = c1; acc[4 * j + 3] = c1; }
        if (has_g1) {
            asm volatile("bar.sync 7, 256;" ::: "memory");
            uint4 v[7];
#pragma unroll
            for (int j = 0; j < 7; j++) v[j] = lds4(xch + j * 2048);
#pragma unroll
            for (int j = 0; j < 7; j++) {
                ub[(7 + j) * 32] = pk(gelu(uf(v[j].x)), gelu(uf(v[j].y)));
                ub[448 + (7 + j) * 32] = pk(gelu(uf(v[j].z)), gelu(uf(v[j].w)));
            }
            asm volatile("bar.arrive 1, 256;" ::: "memory");
            if (lane == 0) mbar_arrive(x_free);
        }
        gemm_loop<1>(acc, sb);
        __nv_bfloat16* o0 = out + (size_t)s0 * 448 + 8 * t;
        mbar_wait0(h_full);
        const uint32_t hs = sb + OFF_A + (60 % NA) * AST + (16 * wq + g) * 224 + t * 4;
#pragma unroll
        for (int hh = 0; hh < 2; hh++) {
            __nv_bfloat16* o = o0 + hh * 8 * 448;
            uint32_t w[14];
#pragma unroll
            for (int j = 0; j < 14; j++) w[j] = hadd2(lds1(hs + hh * 8 * 224 + 16 * j), pk(acc[4 * j + 2 * hh], acc[4 * j + 2 * hh + 1]));
            if ((dt & 1) == 0) {
                o += 112 * dt;
#pragma unroll
                for (int a = 0; a < 3; a++) *(uint4*)(o + 32 * a) = make_uint4(w[4 * a], w[4 * a + 1], w[4 * a + 2], w[4 * a + 3]);
                *(uint2*)(o + 96) = make_uint2(w[12], w[13]);
            } else {
                o += 112 * dt - 16;
                *(uint2*)(o + 4) = make_uint2(w[0], w[1]);
#pragma unroll
                for (int a = 0; a < 3; a++) *(uint4*)(o + 32 + 32 * a) = make_uint4(w[4 * a + 2], w[4 * a + 3], w[4 * a + 4], w[4 * a + 5]);
            }
        }
        __syncwarp();
        mbar_wait0(done + 59 * 8);
    }
}

typedef CUresult (*EncodeFn)(CUtensorMap*, CUtensorMapDataType, cuuint32_t, void*, const cuuint64_t*, const cuuint64_t*,
                             const cuuint32_t*, const cuuint32_t*, CUtensorMapInterleave, CUtensorMapSwizzle,
                             CUtensorMapL2promotion, CUtensorMapFloatOOBfill);

}

extern "C" void kernel_launch(void* const* d_in, const int* in_sizes, int n_in, void* d_out, int out_size) {
    (void)in_sizes; (void)n_in; (void)out_size;
    static EncodeFn enc = nullptr;
    static void* p_tab = nullptr;
    static void* p_scr = nullptr;
    if (!enc) {
        void* fn = nullptr; cudaDriverEntryPointQueryResult qr;
        cudaGetDriverEntryPoint("cuTensorMapEncodeTiled", &fn, cudaEnableDefault, &qr);
        enc = (EncodeFn)fn;
        cudaFuncSetAttribute(fused_kernel, cudaFuncAttributeMaxDynamicSharedMemorySize, SMEM_BYTES);
        cudaGetSymbolAddress(&p_tab, g_tab);
        cudaGetSymbolAddress(&p_scr, g_scr);
    }
    CUtensorMap m1, m2, mr, mi, mh;
    {
        cuuint64_t dim[3] = {1792, 16, 128}; cuuint64_t str[2] = {128ull * 3584, 3584}; cuuint32_t box[3] = {64, 16, 4}, es[3] = {1, 1, 1};
        enc(&m1, CU_TENSOR_MAP_DATA_TYPE_BFLOAT16, 3, d_in[4], dim, str, box, es, CU_TENSOR_MAP_INTERLEAVE_NONE, CU_TENSOR_MAP_SWIZZLE_128B, CU_TENSOR_MAP_L2_PROMOTION_L2_128B, CU_TENSOR_MAP_FLOAT_OOB_FILL_NONE);
    }
    {
        cuuint64_t dim[2] = {2048, 1792}; cuuint64_t str[1] = {4096}; cuuint32_t box[2] = {64, 64}, es[2] = {1, 1};
        enc(&m2, CU_TENSOR_MAP_DATA_TYPE_BFLOAT16, 2, d_in[6], dim, str, box, es, CU_TENSOR_MAP_INTERLEAVE_NONE, CU_TENSOR_MAP_SWIZZLE_128B, CU_TENSOR_MAP_L2_PROMOTION_L2_128B, CU_TENSOR_MAP_FLOAT_OOB_FILL_NONE);
    }
    {
        cuuint64_t dim[2] = {3600, 128}; cuuint64_t str[1] = {7200}; cuuint32_t box[2] = {40, 128}, es[2] = {1, 1};
        enc(&mr, CU_TENSOR_MAP_DATA_TYPE_BFLOAT16, 2, d_in[1], dim, str, box, es, CU_TENSOR_MAP_INTERLEAVE_NONE, CU_TENSOR_MAP_SWIZZLE_NONE, CU_TENSOR_MAP_L2_PROMOTION_NONE, CU_TENSOR_MAP_FLOAT_OOB_FILL_NONE);
        enc(&mi, CU_TENSOR_MAP_DATA_TYPE_BFLOAT16, 2, d_in[2], dim, str, box, es, CU_TENSOR_MAP_INTERLEAVE_NONE, CU_TENSOR_MAP_SWIZZLE_NONE, CU_TENSOR_MAP_L2_PROMOTION_NONE, CU_TENSOR_MAP_FLOAT_OOB_FILL_NONE);
    }
    {
        cuuint64_t dim[2] = {448, 2048}; cuuint64_t str[1] = {896}; cuuint32_t box[2] = {112, 64}, es[2] = {1, 1};
        enc(&mh, CU_TENSOR_MAP_DATA_TYPE_BFLOAT16, 2, ((Scratch*)p_scr)->h, dim, str, box, es, CU_TENSOR_MAP_INTERLEAVE_NONE, CU_TENSOR_MAP_SWIZZLE_NONE, CU_TENSOR_MAP_L2_PROMOTION_NONE, CU_TENSOR_MAP_FLOAT_OOB_FILL_NONE);
    }
    cudaLaunchConfig_t cfg = {};
    cfg.gridDim = dim3(NCTA); cfg.blockDim = dim3(NTHR); cfg.dynamicSmemBytes = SMEM_BYTES; cfg.stream = cudaStreamPerThread;
    cudaLaunchAttribute at[1];
    at[0].id = cudaLaunchAttributeClusterDimension; at[0].val.clusterDim.x = 2; at[0].val.clusterDim.y = 1; at[0].val.clusterDim.z = 1;
    cfg.attrs = at; cfg.numAttrs = 1;

    cudaLaunchKernelEx(&cfg, fused_kernel, (const __nv_bfloat16*)d_in[0], (const uint4*)p_tab, (Scratch*)p_scr,
                       (const __nv_bfloat16*)d_in[5], (const __nv_bfloat16*)d_in[7], (__nv_bfloat16*)d_out, m1, m2, mr, mi, mh);
}
```
